```python
import torch

def _softmax(x, axis=-1):
    return torch.softmax(x, dim=axis)
def _gelu(x):
    return torch.nn.functional.gelu(x, approximate="tanh")
def _silu(x):
    return torch.nn.functional.silu(x)
def _sigmoid(x):
    return torch.sigmoid(x)
def _layernorm(x, axis=-1, eps=1e-5):
    m = x.mean(dim=axis, keepdim=True)
    v = x.var(dim=axis, keepdim=True, unbiased=False)
    return (x - m) / torch.sqrt(v + eps)
def _scatter_add(tgt, idx, src, axis=0):
    return tgt.clone().index_add_(axis, idx, src)
def _segment_sum(src, seg, n):
    out = torch.zeros((n,) + src.shape[1:], dtype=src.dtype)
    return out.index_add_(0, seg, src)
def _pad(x, pw):
    flat = tuple(v for pair in reversed(pw) for v in pair)
    return torch.nn.functional.pad(x, flat)

kernel_name = 'concat_heads__spectral_fnet__sliding_block__prompt'

def setup_inputs():

    _w = (lambda a: (lambda t: t.to(torch.bfloat16) if t.is_floating_point() else t)(torch.as_tensor(a)))
    def _A_setup():
        B, S, D = 1, 2048, 512
        ns = torch.arange(S)[:, None] * torch.arange(S)[None, :]
        nd = torch.arange(D)[:, None] * torch.arange(D)[None, :]
        Ws_re = torch.cos(-2.0 * torch.pi * ns / S).to(float)
        Ws_im = torch.sin(-2.0 * torch.pi * ns / S).to(float)
        Wd_re = torch.cos(-2.0 * torch.pi * nd / D).to(float)
        Wd_im = torch.sin(-2.0 * torch.pi * nd / D).to(float)
        return {
            "x": _w((lambda *s: torch.randn(*s, dtype=torch.bfloat16) * 0.05)(B, S, D)),
            "dft_seq_re": _w(Ws_re),
            "dft_seq_im": _w(Ws_im),
            "dft_hid_re": _w(Wd_re),
            "dft_hid_im": _w(Wd_im),
        }
    _A_in = _A_setup()

    def _B_setup():
        B, S, D = 1, 2048, 512
        return {
            "x": _w((lambda *s: torch.randn(*s, dtype=torch.bfloat16) * 0.2)(B, S, D)),
            "wqkv": _w((lambda *s: torch.randn(*s, dtype=torch.bfloat16) * 0.8)(D, 3 * D)),
            "wo": _w((lambda *s: torch.randn(*s, dtype=torch.bfloat16) * 0.2)(D, D)),
        }
    _B_in = _B_setup()

    return {
        "A_x": _A_in["x"],
        "A_dft_seq_re": _A_in["dft_seq_re"],
        "A_dft_seq_im": _A_in["dft_seq_im"],
        "A_dft_hid_re": _A_in["dft_hid_re"],
        "A_dft_hid_im": _A_in["dft_hid_im"],
        "B_x": _B_in["x"],
        "B_wqkv": _B_in["wqkv"],
        "B_wo": _B_in["wo"],
    }

def reference(A_x, A_dft_seq_re, A_dft_seq_im, A_dft_hid_re, A_dft_hid_im, B_x, B_wqkv, B_wo):
    def _A_ref(x, dft_seq_re, dft_seq_im, dft_hid_re, dft_hid_im):
        a = torch.einsum("bsd,ed->bse", x, dft_hid_re)
        b = torch.einsum("bsd,ed->bse", x, dft_hid_im)
        y = torch.einsum("ts,bse->bte", dft_seq_re, a) - torch.einsum("ts,bse->bte", dft_seq_im, b)
        return y

    def _B_ref(x, wqkv, wo):
        B, S, D = x.shape
        H = 32; Dh = D // H; W = 256
        qkv = (lambda x, *d: x.permute(*d))((x @ wqkv).reshape(B, S, 3, H, Dh), 2, 0, 3, 1, 4)
        q, k, v = qkv[0], qkv[1], qkv[2]
        scores = torch.einsum("bhqd,bhkd->bhqk", q, k) * (Dh ** -0.5)
        idx = torch.arange(S)
        mask = (idx[:, None] - idx[None, :] >= 0) & (idx[:, None] - idx[None, :] < W)
        scores = torch.where(mask[None, None], scores, -1e9)
        p = _softmax(scores, axis=-1)
        o = torch.einsum("bhqk,bhkd->bhqd", p, v)
        return (lambda x, *d: x.permute(*d))(o, 0, 2, 1, 3).reshape(B, S, D) @ wo

    a = _A_ref(A_x, A_dft_seq_re, A_dft_seq_im, A_dft_hid_re, A_dft_hid_im)
    b = _B_ref(B_x, B_wqkv, B_wo)
    return torch.concatenate([a, b], axis=-1)
```

```cpp
#include <cuda_runtime.h>
#include <cuda_bf16.h>
#include <cuda.h>
#include <stdint.h>

#define PHASE_TIMING 0

namespace fk {

constexpr int NCTA = 128;
#define PROLL 0
#define PU1
#define BW 1
#define PF 0
#define PFD 0
#define ABR 32
#define PACE 100
#define AQF 3
#define P2 1
#define HOIST 1
#define KSEQ 1
#define KVC 0
#define PW 1
#define ORD 0
#define PQP 5
#define AFE 1
#define AF3 -4
#define ST0 4
#define STR 2
#define PQE 0
#define S2 0
#define PACE1 150
#define PACE2 200
#define D2 600
#define DPOLL 1200
#define PSTG 300
#define KV0 0
#define KLD 2
#define HS0 8
#define TL 2
#define BS 1
#define HLP 1
#define GAP 150
#define SPC 2048
#define CRL 0
#define SWP 0
#define EXPB 3
#define PKP 0
#define RP 0
#define NOMASK 1
#define NS1 8
#define PQJA 1
#define PQJB 3
#define AF3E 1
constexpr int NS = 9;
constexpr int SLOT = 16384;
constexpr int OFF_Q = NS * SLOT;
constexpr int OFF_KV = OFF_Q + 16384;
constexpr int OFF_X = OFF_KV + 32768;
constexpr int OFF_BAR = OFF_X + 32768;
#define STEPCLK 0
constexpr int SMEM_BYTES = OFF_BAR + 512 + 1024 + (STEPCLK ? 1024 : 0);
constexpr int B_FULL = 0, B_FULL2 = 8, B_EMPTY = 11, B_STGA = B_EMPTY + NS, B_STGB = B_STGA + 1, B_KVFULL = B_STGA + 2, B_KVFREE = B_STGA + 4,
              B_WOFULL = B_STGA + 6, B_EPRDY = B_STGA + 7, B_XFREE = B_STGA + 8, B_KVST = B_STGA + 9, B_WOLATE = B_STGA + 10;
constexpr int B_STGA1 = 31, B_KV0 = 32, B_DONE = 33, B_KVISS = 34, B_RDY = 41;
constexpr int B_HLP = 41;
constexpr int OFF_EP = OFF_BAR + 8 * 40;

__device__ __nv_bfloat16 g_ab[2 * 2048 * 512];
__device__ uint4 g_kv[NCTA * 2048];
__device__ uint4 g_o[32 * 32 * 128];
__device__ uint4 g_part[32 * 16 * 4 * 256];
__device__ unsigned g_cnt[(128 + NCTA) * 32];
__device__ unsigned g_epoch[NCTA];
__device__ const uint4 g_zero[512] = {};
constexpr int C_A1 = 0  , C_KV = 128  ;

struct Params {
  CUtensorMap xa, wdre, wdim, xb, wqkv, wsre, wsim, abld, abst, wo, out;
  const void *p_wsre, *p_wsim, *p_xa, *p_wdre, *p_wdim;
};

__device__ __forceinline__ uint32_t smem_u32(const void* p) { return (uint32_t)__cvta_generic_to_shared(p); }
__device__ __forceinline__ void mbar_init(uint32_t bar, uint32_t cnt) { asm volatile("mbarrier.init.shared::cta.b64 [%0], %1;" ::"r"(bar), "r"(cnt)); }
__device__ __forceinline__ void mbar_expect_tx(uint32_t bar, uint32_t bytes) {
  asm volatile("mbarrier.arrive.expect_tx.shared::cta.b64 _, [%0], %1;" ::"r"(bar), "r"(bytes) : "memory");
}
__device__ __forceinline__ void mbar_arrive(uint32_t bar) { asm volatile("mbarrier.arrive.shared::cta.b64 _, [%0];" ::"r"(bar) : "memory"); }
__device__ __forceinline__ void mbar_arrive_if(uint32_t bar, bool p) {
  asm volatile("{\n.reg .pred q;\nsetp.ne.u32 q, %1, 0;\n@q mbarrier.arrive.shared::cta.b64 _, [%0];\n}" ::"r"(bar), "r"((uint32_t)p) : "memory");
}
__device__ __forceinline__ void mbar_wait(uint32_t bar, uint32_t parity) {
  asm volatile("{\n.reg .pred p, q;\n.reg .u32 it;\nmov.u32 it, 0;\n"
               "WL:\nmbarrier.try_wait.parity.shared::cta.b64 p, [%0], %1;\n@p bra WD;\n"
               "add.u32 it, it, 1;\nsetp.lt.u32 q, it, 4194304;\n@q bra WL;\ntrap;\nWD:\n}" ::"r"(bar), "r"(parity) : "memory");
}
__device__ __forceinline__ void watchdog(uint32_t bar) {
  asm volatile("{\n.reg .pred p, q;\n.reg .u64 t0, t1;\nmov.u64 t0, %%globaltimer;\n"
               "WL:\nmbarrier.try_wait.parity.shared::cta.b64 p, [%0], 0, 1000000;\n@p bra WD;\n"
               "mov.u64 t1, %%globaltimer;\nsub.u64 t1, t1, t0;\nsetp.lt.u64 q, t1, 2000000000;\n@q bra WL;\ntrap;\nWD:\n}" ::"r"(bar) : "memory");
}
__device__ __forceinline__ uint32_t mbar_test(uint32_t bar, uint32_t parity) {
  uint32_t ok;
  asm volatile("{\n.reg .pred p;\nmbarrier.test_wait.parity.shared::cta.b64 p, [%1], %2;\nselp.u32 %0, 1, 0, p;\n}" : "=r"(ok) : "r"(bar), "r"(parity) : "memory");
  return ok;
}
__device__ __forceinline__ void mbar_wait_if(uint32_t ok, uint32_t bar, uint32_t parity) {
  asm volatile("{\n.reg .pred p, q;\n.reg .u32 it;\nsetp.ne.u32 p, %2, 0;\n@p bra WD;\nmov.u32 it, 0;\n"
               "WL:\nmbarrier.try_wait.parity.shared::cta.b64 p, [%0], %1;\n@p bra WD;\n"
               "add.u32 it, it, 1;\nsetp.lt.u32 q, it, 4194304;\n@q bra WL;\ntrap;\nWD:\n}" ::"r"(bar), "r"(parity), "r"(ok) : "memory");
}
__device__ __forceinline__ void tma_ld2(uint32_t dst, const CUtensorMap* tm, int c0, int c1, uint32_t bar) {
  asm volatile("cp.async.bulk.tensor.2d.shared::cluster.global.mbarrier::complete_tx::bytes [%0], [%1, {%3, %4}], [%2];"
               ::"r"(dst), "l"(tm), "r"(bar), "r"(c0), "r"(c1) : "memory");
}
__device__ __forceinline__ void tma_ld3(uint32_t dst, const CUtensorMap* tm, int c0, int c1, int c2, uint32_t bar) {
  asm volatile("cp.async.bulk.tensor.3d.shared::cluster.global.mbarrier::complete_tx::bytes [%0], [%1, {%3, %4, %5}], [%2];"
               ::"r"(dst), "l"(tm), "r"(bar), "r"(c0), "r"(c1), "r"(c2) : "memory");
}
__device__ __forceinline__ void tma_st2(const CUtensorMap* tm, uint32_t src, int c0, int c1) {
  asm volatile("cp.async.bulk.tensor.2d.global.shared::cta.bulk_group [%0, {%2, %3}], [%1];" ::"l"(tm), "r"(src), "r"(c0), "r"(c1) : "memory");
}
__device__ __forceinline__ void bulk_ld(uint32_t dst, const void* src, uint32_t bytes, uint32_t bar) {
  asm volatile("cp.async.bulk.shared::cluster.global.mbarrier::complete_tx::bytes [%0], [%1], %2, [%3];"
               ::"r"(dst), "l"(src), "r"(bytes), "r"(bar) : "memory");
}
__device__ __forceinline__ void bulk_st(void* dst, uint32_t src, uint32_t bytes) {
  asm volatile("cp.async.bulk.global.shared::cta.bulk_group [%0], [%1], %2;" ::"l"(dst), "r"(src), "r"(bytes) : "memory");
}
__device__ __forceinline__ void bar_sync(int id, int n) { asm volatile("bar.sync %0, %1;" ::"r"(id), "r"(n) : "memory"); }
__device__ __forceinline__ void bar_arrive(int id, int n) { asm volatile("bar.arrive %0, %1;" ::"r"(id), "r"(n) : "memory"); }
__device__ __forceinline__ void bulk_commit() { asm volatile("cp.async.bulk.commit_group;" ::: "memory"); }
template <int N> __device__ __forceinline__ void bulk_wait() { asm volatile("cp.async.bulk.wait_group %0;" ::"n"(N) : "memory"); }
__device__ __forceinline__ void bulk_wait_read() { asm volatile("cp.async.bulk.wait_group.read 0;" ::: "memory"); }
__device__ __forceinline__ void l2_prefetch2(const CUtensorMap* tm, int c0, int c1) {
  asm volatile("cp.async.bulk.prefetch.tensor.2d.L2.global.tile [%0, {%1, %2}];" ::"l"(tm), "r"(c0), "r"(c1) : "memory");
}
__device__ __forceinline__ void l2_prefetch(const void* p, uint32_t bytes) {
  asm volatile("cp.async.bulk.prefetch.L2.global [%0], %1;" ::"l"(p), "r"(bytes) : "memory");
}
__device__ __forceinline__ void prefetch_tmap(const CUtensorMap* tm) { asm volatile("prefetch.tensormap [%0];" ::"l"(tm) : "memory"); }
__device__ __forceinline__ void fence_async_smem() { asm volatile("fence.proxy.async.shared::cta;" ::: "memory"); }
__device__ __forceinline__ void fence_async_glb() { asm volatile("fence.proxy.async.global;" ::: "memory"); }
__device__ __forceinline__ void wgmma_fence() { asm volatile("wgmma.fence.sync.aligned;" ::: "memory"); }
__device__ __forceinline__ void wgmma_commit() { asm volatile("wgmma.commit_group.sync.aligned;" ::: "memory"); }
template <int N> __device__ __forceinline__ void wgmma_wait() { asm volatile("wgmma.wait_group.sync.aligned %0;" ::"n"(N) : "memory"); }
template <int N> __device__ __forceinline__ void reg_fence(float (&d)[N]) {
#pragma unroll
  for (int i = 0; i < N; i++) asm volatile("" : "+f"(d[i])::"memory");
}
__device__ __forceinline__ bool elect_one() {
  uint32_t p;
  asm volatile("{\n.reg .pred P;\nelect.sync _|P, 0xffffffff;\nselp.b32 %0, 1, 0, P;\n}" : "=r"(p));
  return p;
}
__device__ __forceinline__ void stsm4(uint32_t addr, uint32_t r0, uint32_t r1, uint32_t r2, uint32_t r3) {
  asm volatile("stmatrix.sync.aligned.m8n8.x4.shared.b16 [%0], {%1,%2,%3,%4};" ::"r"(addr), "r"(r0), "r"(r1), "r"(r2), "r"(r3) : "memory");
}
__device__ __forceinline__ void ldsm4(uint32_t (&r)[4], uint32_t addr) {
  asm volatile("ldmatrix.sync.aligned.m8n8.x4.shared.b16 {%0,%1,%2,%3}, [%4];" : "=r"(r[0]), "=r"(r[1]), "=r"(r[2]), "=r"(r[3]) : "r"(addr) : "memory");
}
__device__ __forceinline__ uint32_t pack_bf16(float lo, float hi) {
  uint32_t r;
  asm("cvt.rn.bf16x2.f32 %0, %1, %2;" : "=r"(r) : "f"(hi), "f"(lo));
  return r;
}
__device__ __forceinline__ float ex2(float x) { float y; asm("ex2.approx.ftz.f32 %0, %1;" : "=f"(y) : "f"(x)); return y; }
__device__ __forceinline__ float rcp(float x) { float y; asm("rcp.approx.ftz.f32 %0, %1;" : "=f"(y) : "f"(x)); return y; }
#define FV 4
#define FVA FV
template <int FV_> __device__ __forceinline__ void red_release(unsigned* p) {
  if (FV_ == 0) asm volatile("fence.proxy.async;\nfence.acq_rel.gpu;\nred.relaxed.gpu.global.add.u32 [%0], 1;" ::"l"(p) : "memory");
  if (FV_ == 1) asm volatile("fence.acq_rel.gpu;\nred.relaxed.gpu.global.add.u32 [%0], 1;" ::"l"(p) : "memory");
  if (FV_ == 2) asm volatile("red.relaxed.gpu.global.add.u32 [%0], 1;" ::"l"(p) : "memory");
  if (FV_ == 3) asm volatile("fence.proxy.async;\nred.relaxed.gpu.global.add.u32 [%0], 1;" ::"l"(p) : "memory");
  if (FV_ == 4) asm volatile("red.release.gpu.global.add.u32 [%0], 1;" ::"l"(p) : "memory");
  if (FV_ == 5) asm volatile("fence.release.gpu;\nred.relaxed.gpu.global.add.u32 [%0], 1;" ::"l"(p) : "memory");
}
__device__ __forceinline__ void poll_ge(const unsigned* p, unsigned target) {
  asm volatile("{\n.reg .pred p;\n.reg .u32 v;\n"
               "PL:\nld.relaxed.gpu.global.u32 v, [%0];\nsub.u32 v, v, %1;\nsetp.lt.s32 p, v, 0;\n@p bra PL;\nfence.acquire.gpu;\n}" ::"l"(p), "r"(target) : "memory");
}
__device__ __forceinline__ void poll2_ge(const unsigned* p0, const unsigned* p1, unsigned target) {
  asm volatile("{\n.reg .pred p;\n.reg .u32 v, w;\n"
               "PL:\nld.relaxed.gpu.global.u32 v, [%0];\nld.relaxed.gpu.global.u32 w, [%1];\n"
               "sub.u32 v, v, %2;\nsub.u32 w, w, %2;\nor.b32 v, v, w;\nsetp.lt.s32 p, v, 0;\n@p bra PL;\nfence.acquire.gpu;\n}"
               ::"l"(p0), "l"(p1), "r"(target) : "memory");
}
__device__ __forceinline__ void ld_pkt(const uint4* p, uint32_t* a) {
  asm volatile("{\n.reg .b128 t;\nld.relaxed.gpu.global.b128 t, [%4];\nmov.b128 {%0,%1,%2,%3}, t;\n}"
               : "=r"(a[0]), "=r"(a[1]), "=r"(a[2]), "=r"(a[3]) : "l"(p) : "memory");
}
__device__ __forceinline__ void ldt_pkt(const uint4* p, uint32_t* a) {
  asm volatile("{\n.reg .b128 t;\nld.relaxed.gpu.global.b128 t, [%4];\nmov.b128 {%0,%1,%2,%3}, t;\n}"
               : "+r"(a[0]), "+r"(a[1]), "+r"(a[2]), "+r"(a[3]) : "l"(p) : "memory");
}
__device__ __forceinline__ void ldp_pkt(const uint4* p, uint32_t* a, uint32_t again) {
  asm volatile("{\n.reg .b128 t;\n.reg .pred q;\nsetp.ne.u32 q, %5, 0;\n"
               "mov.b128 t, {%0,%1,%2,%3};\n@q ld.relaxed.gpu.global.b128 t, [%4];\nmov.b128 {%0,%1,%2,%3}, t;\n}"
               : "+r"(a[0]), "+r"(a[1]), "+r"(a[2]), "+r"(a[3]) : "l"(p), "r"(again) : "memory");
}
#define PKT_WAIT(dbg, n0, n1, arr, PTR) { \
    uint32_t again_; \
    asm volatile("mov.u32 %0, 0;" : "=r"(again_)); \
    uint32_t it_ = 0; \
    _Pragma("unroll 1") do { \
      uint32_t bad_ = 0; \
      _Pragma("unroll") for (int i = n0; i < n1; i++) ldp_pkt(PTR, arr[i], again_); \
      _Pragma("unroll") for (int i = n0; i < n1; i++) bad_ |= arr[i][0] ^ tag; \
      again_ = __any_sync(0xffffffffu, bad_ & 1); \
      it_++; \
    } while (again_); \
    DBGIT(dbg, it_ - 1); }
__device__ __forceinline__ void re_pkt(const uint4* p, uint32_t* a, uint32_t tag) {
  asm volatile("{\n.reg .b128 t;\n.reg .pred q;\n.reg .b32 x;\nxor.b32 x, %0, %5;\nand.b32 x, x, 1;\nsetp.ne.u32 q, x, 0;\n"
               "mov.b128 t, {%0,%1,%2,%3};\n@q ld.relaxed.gpu.global.b128 t, [%4];\nmov.b128 {%0,%1,%2,%3}, t;\n}"
               : "+r"(a[0]), "+r"(a[1]), "+r"(a[2]), "+r"(a[3]) : "l"(p), "r"(tag) : "memory");
}
__device__ __forceinline__ uint32_t tag_pkt(uint32_t a0, uint32_t tag) {
  a0 -= tag;
  return ((a0 + ((a0 >> 1) & 1)) & ~1u) + tag;
}
__device__ __forceinline__ void st_pkt(uint4* p, uint32_t a0, uint32_t a1, uint32_t a2, uint32_t a3, uint32_t tag) {
  a0 = tag_pkt(a0, tag);
  asm volatile("{\n.reg .b128 t;\nmov.b128 t, {%1,%2,%3,%4};\nst.relaxed.gpu.global.b128 [%0], t;\n}" ::"l"(p), "r"(a0), "r"(a1), "r"(a2), "r"(a3) : "memory");
}
__device__ __forceinline__ void st_pkt_if(uint4* p, uint32_t a0, uint32_t a1, uint32_t a2, uint32_t a3, uint32_t tag, bool c) {
  a0 = tag_pkt(a0, tag);
  asm volatile("{\n.reg .b128 t;\n.reg .pred q;\nsetp.ne.u32 q, %5, 0;\nmov.b128 t, {%1,%2,%3,%4};\n@q st.relaxed.gpu.global.b128 [%0], t;\n}"
               ::"l"(p), "r"(a0), "r"(a1), "r"(a2), "r"(a3), "r"((uint32_t)c) : "memory");
}
__device__ __forceinline__ uint64_t mkd(uint32_t lo, uint32_t hi) { return ((uint64_t)hi << 32) | lo; }
constexpr uint32_t HI128 = 64u | (1u << 30), HI32 = 16u | (3u << 30);
__device__ __forceinline__ uint32_t dlo(uint32_t addr, uint32_t lbo16) { return ((addr & 0x3FFFF) >> 4) | (lbo16 << 16); }
__device__ __forceinline__ uint64_t desc_k128(uint32_t a) { return mkd(dlo(a, 1), HI128); }
__device__ __forceinline__ uint64_t desc_mn128(uint32_t a, uint32_t lbo16) { return mkd(dlo(a, lbo16), HI128); }

__device__ __forceinline__ void wgmma_ss_n128(float (&d)[64], uint64_t da, uint64_t db, int sd) {
  asm volatile("{\n.reg .pred p;\nsetp.ne.b32 p, %66, 0;\n"
    "wgmma.mma_async.sync.aligned.m64n128k16.f32.bf16.bf16 {"
    "%0,%1,%2,%3,%4,%5,%6,%7,%8,%9,%10,%11,%12,%13,%14,%15,%16,%17,%18,%19,%20,%21,%22,%23,%24,%25,%26,%27,%28,%29,%30,%31,%32,%33,%34,%35,%36,%37,%38,%39,"
    "%40,%41,%42,%43,%44,%45,%46,%47,%48,%49,%50,%51,%52,%53,%54,%55,%56,%57,%58,%59,%60,%61,%62,%63"
    "}, %64, %65, p, 1, 1, 0, 0;\n}\n"
    : "+f"(d[0]),"+f"(d[1]),"+f"(d[2]),"+f"(d[3]),"+f"(d[4]),"+f"(d[5]),"+f"(d[6]),"+f"(d[7]),"+f"(d[8]),"+f"(d[9]),"+f"(d[10]),"+f"(d[11]),"+f"(d[12]),
      "+f"(d[13]),"+f"(d[14]),"+f"(d[15]),"+f"(d[16]),"+f"(d[17]),"+f"(d[18]),"+f"(d[19]),"+f"(d[20]),"+f"(d[21]),"+f"(d[22]),"+f"(d[23]),"+f"(d[24]),
      "+f"(d[25]),"+f"(d[26]),"+f"(d[27]),"+f"(d[28]),"+f"(d[29]),"+f"(d[30]),"+f"(d[31]),"+f"(d[32]),"+f"(d[33]),"+f"(d[34]),"+f"(d[35]),"+f"(d[36]),
      "+f"(d[37]),"+f"(d[38]),"+f"(d[39]),"+f"(d[40]),"+f"(d[41]),"+f"(d[42]),"+f"(d[43]),"+f"(d[44]),"+f"(d[45]),"+f"(d[46]),"+f"(d[47]),"+f"(d[48]),
      "+f"(d[49]),"+f"(d[50]),"+f"(d[51]),"+f"(d[52]),"+f"(d[53]),"+f"(d[54]),"+f"(d[55]),"+f"(d[56]),"+f"(d[57]),"+f"(d[58]),"+f"(d[59]),"+f"(d[60]),
      "+f"(d[61]),"+f"(d[62]),"+f"(d[63])
    : "l"(da), "l"(db), "r"(sd));
}
__device__ __forceinline__ void wgmma_ss_n128t(float (&d)[64], uint64_t da, uint64_t db, int sd) {
  asm volatile("{\n.reg .pred p;\nsetp.ne.b32 p, %66, 0;\n"
    "wgmma.mma_async.sync.aligned.m64n128k16.f32.bf16.bf16 {"
    "%0,%1,%2,%3,%4,%5,%6,%7,%8,%9,%10,%11,%12,%13,%14,%15,%16,%17,%18,%19,%20,%21,%22,%23,%24,%25,%26,%27,%28,%29,%30,%31,%32,%33,%34,%35,%36,%37,%38,%39,"
    "%40,%41,%42,%43,%44,%45,%46,%47,%48,%49,%50,%51,%52,%53,%54,%55,%56,%57,%58,%59,%60,%61,%62,%63"
    "}, %64, %65, p, 1, 1, 0, 1;\n}\n"
    : "+f"(d[0]),"+f"(d[1]),"+f"(d[2]),"+f"(d[3]),"+f"(d[4]),"+f"(d[5]),"+f"(d[6]),"+f"(d[7]),"+f"(d[8]),"+f"(d[9]),"+f"(d[10]),"+f"(d[11]),"+f"(d[12]),
      "+f"(d[13]),"+f"(d[14]),"+f"(d[15]),"+f"(d[16]),"+f"(d[17]),"+f"(d[18]),"+f"(d[19]),"+f"(d[20]),"+f"(d[21]),"+f"(d[22]),"+f"(d[23]),"+f"(d[24]),
      "+f"(d[25]),"+f"(d[26]),"+f"(d[27]),"+f"(d[28]),"+f"(d[29]),"+f"(d[30]),"+f"(d[31]),"+f"(d[32]),"+f"(d[33]),"+f"(d[34]),"+f"(d[35]),"+f"(d[36]),
      "+f"(d[37]),"+f"(d[38]),"+f"(d[39]),"+f"(d[40]),"+f"(d[41]),"+f"(d[42]),"+f"(d[43]),"+f"(d[44]),"+f"(d[45]),"+f"(d[46]),"+f"(d[47]),"+f"(d[48]),
      "+f"(d[49]),"+f"(d[50]),"+f"(d[51]),"+f"(d[52]),"+f"(d[53]),"+f"(d[54]),"+f"(d[55]),"+f"(d[56]),"+f"(d[57]),"+f"(d[58]),"+f"(d[59]),"+f"(d[60]),
      "+f"(d[61]),"+f"(d[62]),"+f"(d[63])
    : "l"(da), "l"(db), "r"(sd));
}
__device__ __forceinline__ void wgmma_ss_n192(float (&d)[96], uint64_t da, uint64_t db, int sd) {
  asm volatile("{\n.reg .pred p;\nsetp.ne.b32 p, %98, 0;\n"
    "wgmma.mma_async.sync.aligned.m64n192k16.f32.bf16.bf16 {"
    "%0,%1,%2,%3,%4,%5,%6,%7,%8,%9,%10,%11,%12,%13,%14,%15,%16,%17,%18,%19,%20,%21,%22,%23,%24,%25,%26,%27,%28,%29,%30,%31,%32,%33,%34,%35,%36,%37,%38,%39,"
    "%40,%41,%42,%43,%44,%45,%46,%47,%48,%49,%50,%51,%52,%53,%54,%55,%56,%57,%58,%59,%60,%61,%62,%63,%64,%65,%66,%67,%68,%69,%70,%71,%72,%73,%74,%75,%76,"
    "%77,%78,%79,%80,%81,%82,%83,%84,%85,%86,%87,%88,%89,%90,%91,%92,%93,%94,%95"
    "}, %96, %97, p, 1, 1, 0, 1;\n}\n"
    : "+f"(d[0]),"+f"(d[1]),"+f"(d[2]),"+f"(d[3]),"+f"(d[4]),"+f"(d[5]),"+f"(d[6]),"+f"(d[7]),"+f"(d[8]),"+f"(d[9]),"+f"(d[10]),"+f"(d[11]),"+f"(d[12]),
      "+f"(d[13]),"+f"(d[14]),"+f"(d[15]),"+f"(d[16]),"+f"(d[17]),"+f"(d[18]),"+f"(d[19]),"+f"(d[20]),"+f"(d[21]),"+f"(d[22]),"+f"(d[23]),"+f"(d[24]),
      "+f"(d[25]),"+f"(d[26]),"+f"(d[27]),"+f"(d[28]),"+f"(d[29]),"+f"(d[30]),"+f"(d[31]),"+f"(d[32]),"+f"(d[33]),"+f"(d[34]),"+f"(d[35]),"+f"(d[36]),
      "+f"(d[37]),"+f"(d[38]),"+f"(d[39]),"+f"(d[40]),"+f"(d[41]),"+f"(d[42]),"+f"(d[43]),"+f"(d[44]),"+f"(d[45]),"+f"(d[46]),"+f"(d[47]),"+f"(d[48]),
      "+f"(d[49]),"+f"(d[50]),"+f"(d[51]),"+f"(d[52]),"+f"(d[53]),"+f"(d[54]),"+f"(d[55]),"+f"(d[56]),"+f"(d[57]),"+f"(d[58]),"+f"(d[59]),"+f"(d[60]),
      "+f"(d[61]),"+f"(d[62]),"+f"(d[63]),"+f"(d[64]),"+f"(d[65]),"+f"(d[66]),"+f"(d[67]),"+f"(d[68]),"+f"(d[69]),"+f"(d[70]),"+f"(d[71]),"+f"(d[72]),
      "+f"(d[73]),"+f"(d[74]),"+f"(d[75]),"+f"(d[76]),"+f"(d[77]),"+f"(d[78]),"+f"(d[79]),"+f"(d[80]),"+f"(d[81]),"+f"(d[82]),"+f"(d[83]),"+f"(d[84]),
      "+f"(d[85]),"+f"(d[86]),"+f"(d[87]),"+f"(d[88]),"+f"(d[89]),"+f"(d[90]),"+f"(d[91]),"+f"(d[92]),"+f"(d[93]),"+f"(d[94]),"+f"(d[95])
    : "l"(da), "l"(db), "r"(sd));
}
__device__ __forceinline__ void wgmma_ss_n256(float (&d)[128], uint64_t da, uint64_t db, int sd) {
  asm volatile("{\n.reg .pred p;\nsetp.ne.b32 p, %130, 0;\n"
    "wgmma.mma_async.sync.aligned.m64n256k16.f32.bf16.bf16 {"
    "%0,%1,%2,%3,%4,%5,%6,%7,%8,%9,%10,%11,%12,%13,%14,%15,%16,%17,%18,%19,%20,%21,%22,%23,%24,%25,%26,%27,%28,%29,%30,%31,%32,%33,%34,%35,%36,%37,%38,%39,"
    "%40,%41,%42,%43,%44,%45,%46,%47,%48,%49,%50,%51,%52,%53,%54,%55,%56,%57,%58,%59,%60,%61,%62,%63,%64,%65,%66,%67,%68,%69,%70,%71,%72,%73,%74,%75,%76,"
    "%77,%78,%79,%80,%81,%82,%83,%84,%85,%86,%87,%88,%89,%90,%91,%92,%93,%94,%95,%96,%97,%98,%99,%100,%101,%102,%103,%104,%105,%106,%107,%108,%109,%110,"
    "%111,%112,%113,%114,%115,%116,%117,%118,%119,%120,%121,%122,%123,%124,%125,%126,%127"
    "}, %128, %129, p, 1, 1, 0, 1;\n}\n"
    : "+f"(d[0]),"+f"(d[1]),"+f"(d[2]),"+f"(d[3]),"+f"(d[4]),"+f"(d[5]),"+f"(d[6]),"+f"(d[7]),"+f"(d[8]),"+f"(d[9]),"+f"(d[10]),"+f"(d[11]),"+f"(d[12]),
      "+f"(d[13]),"+f"(d[14]),"+f"(d[15]),"+f"(d[16]),"+f"(d[17]),"+f"(d[18]),"+f"(d[19]),"+f"(d[20]),"+f"(d[21]),"+f"(d[22]),"+f"(d[23]),"+f"(d[24]),
      "+f"(d[25]),"+f"(d[26]),"+f"(d[27]),"+f"(d[28]),"+f"(d[29]),"+f"(d[30]),"+f"(d[31]),"+f"(d[32]),"+f"(d[33]),"+f"(d[34]),"+f"(d[35]),"+f"(d[36]),
      "+f"(d[37]),"+f"(d[38]),"+f"(d[39]),"+f"(d[40]),"+f"(d[41]),"+f"(d[42]),"+f"(d[43]),"+f"(d[44]),"+f"(d[45]),"+f"(d[46]),"+f"(d[47]),"+f"(d[48]),
      "+f"(d[49]),"+f"(d[50]),"+f"(d[51]),"+f"(d[52]),"+f"(d[53]),"+f"(d[54]),"+f"(d[55]),"+f"(d[56]),"+f"(d[57]),"+f"(d[58]),"+f"(d[59]),"+f"(d[60]),
      "+f"(d[61]),"+f"(d[62]),"+f"(d[63]),"+f"(d[64]),"+f"(d[65]),"+f"(d[66]),"+f"(d[67]),"+f"(d[68]),"+f"(d[69]),"+f"(d[70]),"+f"(d[71]),"+f"(d[72]),
      "+f"(d[73]),"+f"(d[74]),"+f"(d[75]),"+f"(d[76]),"+f"(d[77]),"+f"(d[78]),"+f"(d[79]),"+f"(d[80]),"+f"(d[81]),"+f"(d[82]),"+f"(d[83]),"+f"(d[84]),
      "+f"(d[85]),"+f"(d[86]),"+f"(d[87]),"+f"(d[88]),"+f"(d[89]),"+f"(d[90]),"+f"(d[91]),"+f"(d[92]),"+f"(d[93]),"+f"(d[94]),"+f"(d[95]),"+f"(d[96]),
      "+f"(d[97]),"+f"(d[98]),"+f"(d[99]),"+f"(d[100]),"+f"(d[101]),"+f"(d[102]),"+f"(d[103]),"+f"(d[104]),"+f"(d[105]),"+f"(d[106]),"+f"(d[107]),
      "+f"(d[108]),"+f"(d[109]),"+f"(d[110]),"+f"(d[111]),"+f"(d[112]),"+f"(d[113]),"+f"(d[114]),"+f"(d[115]),"+f"(d[116]),"+f"(d[117]),"+f"(d[118]),
      "+f"(d[119]),"+f"(d[120]),"+f"(d[121]),"+f"(d[122]),"+f"(d[123]),"+f"(d[124]),"+f"(d[125]),"+f"(d[126]),"+f"(d[127])
    : "l"(da), "l"(db), "r"(sd));
}
__device__ __forceinline__ void wgmma_rs_n16k(float (&d)[8], uint32_t a0, uint32_t a1, uint32_t a2, uint32_t a3, uint64_t db, int sd) {
  asm volatile("{\n.reg .pred p;\nsetp.ne.b32 p, %13, 0;\n"
    "wgmma.mma_async.sync.aligned.m64n16k16.f32.bf16.bf16 {"
    "%0,%1,%2,%3,%4,%5,%6,%7"
    "}, {%8,%9,%10,%11}, %12, p, 1, 1, 0;\n}\n"
    : "+f"(d[0]),"+f"(d[1]),"+f"(d[2]),"+f"(d[3]),"+f"(d[4]),"+f"(d[5]),"+f"(d[6]),"+f"(d[7])
    : "r"(a0), "r"(a1), "r"(a2), "r"(a3), "l"(db), "r"(sd));
}
__device__ __forceinline__ void wgmma_rs_n32k(float (&d)[16], uint32_t a0, uint32_t a1, uint32_t a2, uint32_t a3, uint64_t db, int sd) {
  asm volatile("{\n.reg .pred p;\nsetp.ne.b32 p, %21, 0;\n"
    "wgmma.mma_async.sync.aligned.m64n32k16.f32.bf16.bf16 {"
    "%0,%1,%2,%3,%4,%5,%6,%7,%8,%9,%10,%11,%12,%13,%14,%15"
    "}, {%16,%17,%18,%19}, %20, p, 1, 1, 0;\n}\n"
    : "+f"(d[0]),"+f"(d[1]),"+f"(d[2]),"+f"(d[3]),"+f"(d[4]),"+f"(d[5]),"+f"(d[6]),"+f"(d[7]),"+f"(d[8]),"+f"(d[9]),"+f"(d[10]),"+f"(d[11]),"+f"(d[12]),
      "+f"(d[13]),"+f"(d[14]),"+f"(d[15])
    : "r"(a0), "r"(a1), "r"(a2), "r"(a3), "l"(db), "r"(sd));
}
__device__ __forceinline__ void wgmma_rs_n16(float (&d)[8], uint32_t a0, uint32_t a1, uint32_t a2, uint32_t a3, uint64_t db, int sd) {
  asm volatile("{\n.reg .pred p;\nsetp.ne.b32 p, %13, 0;\n"
    "wgmma.mma_async.sync.aligned.m64n16k16.f32.bf16.bf16 {"
    "%0,%1,%2,%3,%4,%5,%6,%7"
    "}, {%8,%9,%10,%11}, %12, p, 1, 1, 1;\n}\n"
    : "+f"(d[0]),"+f"(d[1]),"+f"(d[2]),"+f"(d[3]),"+f"(d[4]),"+f"(d[5]),"+f"(d[6]),"+f"(d[7])
    : "r"(a0), "r"(a1), "r"(a2), "r"(a3), "l"(db), "r"(sd));
}
__device__ __forceinline__ void wgmma_rs_n128(float (&d)[64], uint32_t a0, uint32_t a1, uint32_t a2, uint32_t a3, uint64_t db, int sd) {
  asm volatile("{\n.reg .pred p;\nsetp.ne.b32 p, %69, 0;\n"
    "wgmma.mma_async.sync.aligned.m64n128k16.f32.bf16.bf16 {"
    "%0,%1,%2,%3,%4,%5,%6,%7,%8,%9,%10,%11,%12,%13,%14,%15,%16,%17,%18,%19,%20,%21,%22,%23,%24,%25,%26,%27,%28,%29,%30,%31,%32,%33,%34,%35,%36,%37,%38,%39,"
    "%40,%41,%42,%43,%44,%45,%46,%47,%48,%49,%50,%51,%52,%53,%54,%55,%56,%57,%58,%59,%60,%61,%62,%63"
    "}, {%64,%65,%66,%67}, %68, p, 1, 1, 1;\n}\n"
    : "+f"(d[0]),"+f"(d[1]),"+f"(d[2]),"+f"(d[3]),"+f"(d[4]),"+f"(d[5]),"+f"(d[6]),"+f"(d[7]),"+f"(d[8]),"+f"(d[9]),"+f"(d[10]),"+f"(d[11]),"+f"(d[12]),
      "+f"(d[13]),"+f"(d[14]),"+f"(d[15]),"+f"(d[16]),"+f"(d[17]),"+f"(d[18]),"+f"(d[19]),"+f"(d[20]),"+f"(d[21]),"+f"(d[22]),"+f"(d[23]),"+f"(d[24]),
      "+f"(d[25]),"+f"(d[26]),"+f"(d[27]),"+f"(d[28]),"+f"(d[29]),"+f"(d[30]),"+f"(d[31]),"+f"(d[32]),"+f"(d[33]),"+f"(d[34]),"+f"(d[35]),"+f"(d[36]),
      "+f"(d[37]),"+f"(d[38]),"+f"(d[39]),"+f"(d[40]),"+f"(d[41]),"+f"(d[42]),"+f"(d[43]),"+f"(d[44]),"+f"(d[45]),"+f"(d[46]),"+f"(d[47]),"+f"(d[48]),
      "+f"(d[49]),"+f"(d[50]),"+f"(d[51]),"+f"(d[52]),"+f"(d[53]),"+f"(d[54]),"+f"(d[55]),"+f"(d[56]),"+f"(d[57]),"+f"(d[58]),"+f"(d[59]),"+f"(d[60]),
      "+f"(d[61]),"+f"(d[62]),"+f"(d[63])
    : "r"(a0), "r"(a1), "r"(a2), "r"(a3), "l"(db), "r"(sd));
}

#define STAMP(i)
#define STAMPB(i)
#define STAMPT(i)
#define DBGIT(i, v)
#define CLK(i)
#define CLKDECL
#define CLKDUMP

#define SCLK(i)
#define SGT(i)
#define SCLKP(i)
#define SCLKF(i)
#define SCLKC(i) SCLK(i)
#define WD 1
#define FINS 0
#define HOLD 5
#define ROLL 0
#define RETRY_LOOP _Pragma("unroll 1") for (;;)
__device__ __forceinline__ uint32_t nxt(uint32_t s) { return s == NS - 1 ? 0 : s + 1; }

__device__ __forceinline__ void stage64(uint32_t base, const float* a, int warp_in_wg, int lane, uint32_t sgn = 0) {
  int row = warp_in_wg * 16 + (lane & 7) + ((lane >> 3) & 1) * 8;
  uint32_t rb = base + row * 128;
#pragma unroll
  for (int j = 0; j < 4; j++) {
    int chunk = 2 * j + (lane >> 4);
    stsm4(rb + ((chunk ^ (row & 7)) << 4), pack_bf16(a[8 * j + 0], a[8 * j + 1]) ^ sgn, pack_bf16(a[8 * j + 2], a[8 * j + 3]) ^ sgn,
          pack_bf16(a[8 * j + 4], a[8 * j + 5]) ^ sgn, pack_bf16(a[8 * j + 6], a[8 * j + 7]) ^ sgn);
  }
}

#define A1_STORE(half, pace) { \
    const int row = (tg1 >> 2) * 2048 + ti1 * 128 + (half) * 64, kq = (tg1 >> 2) * 2 + (ti1 >> 3); \
    const int col0 = (tg1 & 2) * 128 + (((tg1 & 1) * 2 - kq - (TL == 2)) & 3) * 64, col1 = (tg1 & 2) * 128 + (((tg1 & 1) * 2 + 1 - kq - (TL == 2)) & 3) * 64; \
    const uint32_t x = sbase + OFF_X + (half) * 16384; \
    _Pragma("unroll") for (int i = 0; i < 16384 / (ABR * 128); i++) { \
      tma_st2(&P.abst, x + i * ABR * 128, ((i * ABR) >> 6) ? col1 : col0, row + ((i * ABR) & 63)); \
      if ((pace) > 0 && i + 1 < 16384 / (ABR * 128)) __nanosleep(pace); \
    } \
    bulk_commit(); \
    bulk_wait<0>(); \
    mbar_arrive(BAR(B_XFREE)); \
    red_release<FVA>(&g_cnt[(C_A1 + (kq * 16 + (ti1 & 7) * 2 + (half)) * 2 + ((tg1 >> 1) & 1)) * 32]); }
#define PFW 0
#define PFB 3
#define PFP 0
#define TMPF 1
#define EEL 0
#define PF0 0
#define PF0M 0
#define LMAP 0
#define IFENCE 0
#define INIT_FENCE() asm volatile("fence.mbarrier_init.release.cluster;" ::: "memory")
#define CSB 1
#define EARLY 4
#define EARLY_U 0
#define CL 0
#define MAPA 06543210
#define MAPB 06510432
#define MAP2 06543210
#define MAP3 06543210
__device__ __forceinline__ int perm7(int b, unsigned code) {
  int r = 0;
#pragma unroll
  for (int i = 0; i < 7; i++) r |= ((b >> ((code >> (3 * i)) & 7)) & 1) << i;
  return r;
}
__device__ __noinline__ void redo_units(uint32_t badmask, uint32_t tag, uint32_t sbase, int tid, int wg, int ti, int tg) {
  const int wq = tid >> 5, lane = tid & 31;

        const float CS = 0.25f * 1.4426950408889634f;
        mbar_wait(sbase + OFF_BAR + 8 * B_KVST, 0);
        for (int u = 0; u < 4; u++) {
          if (!((badmask >> u) & 1)) continue;
          uint32_t res[4];
#pragma unroll
          for (int rr = 0; rr < 2; rr++) {
            const int row = wg * 64 + wq * 16 + (lane >> 2) + 8 * rr, gi = ti * 128 + row;
            uint32_t qq[8];
#pragma unroll
            for (int h = 0; h < 2; h++)
              asm volatile("ld.shared.v4.u32 {%0,%1,%2,%3}, [%4];" : "=r"(qq[4 * h]), "=r"(qq[4 * h + 1]), "=r"(qq[4 * h + 2]), "=r"(qq[4 * h + 3])
                           : "r"(sbase + OFF_Q + row * 128 + (((2 * u + h) ^ (row & 7)) << 4)) : "memory");
            float m = -INFINITY, l = 0.f, o0 = 0.f, o1 = 0.f, o2 = 0.f, o3 = 0.f;
            for (int j = max(0, gi - 255); j <= gi; j++) {
              const int r = j & 127, sw = (r >> 2) & 1;
              const uint4* kp = g_kv + (size_t)((j >> 7) * 8 + tg) * 2048 + u * 512 + r * 2;
              const uint4 k0 = __ldcg(kp + sw), k1 = __ldcg(kp + (sw ^ 1));
              const uint32_t kk[8] = {k0.x, k0.y, k0.z, k0.w, k1.x, k1.y, k1.z, k1.w};
              float s = 0.f;
#pragma unroll
              for (int e = 0; e < 8; e++) {
                s = fmaf(__uint_as_float(qq[e] << 16), __uint_as_float(kk[e] << 16), s);
                s = fmaf(__uint_as_float(qq[e] & 0xffff0000u), __uint_as_float(kk[e] & 0xffff0000u), s);
              }
              s *= CS;
              const uint32_t v0 = __ldcg((const uint32_t*)(kp + 256 + sw) + (lane & 3)), v1 = __ldcg((const uint32_t*)(kp + 256 + (sw ^ 1)) + (lane & 3));
              const float mn = fmaxf(m, s), corr = ex2(m - mn), p = ex2(s - mn);
              m = mn;
              l = fmaf(l, corr, p);
              o0 = fmaf(o0, corr, p * __uint_as_float(v0 << 16)); o1 = fmaf(o1, corr, p * __uint_as_float(v0 & 0xffff0000u));
              o2 = fmaf(o2, corr, p * __uint_as_float(v1 << 16)); o3 = fmaf(o3, corr, p * __uint_as_float(v1 & 0xffff0000u));
            }
            l = 1.f / l;
            res[rr] = pack_bf16(o0 * l, o1 * l); res[2 + rr] = pack_bf16(o2 * l, o3 * l);
          }
          st_pkt(g_o + (size_t)((2 * ti + wg) * 32 + 4 * tg + u) * 128 + tid, res[0], res[1], res[2], res[3], tag);
        }
        __syncwarp();
}

__global__ void
__launch_bounds__(384, 1) fused_kernel(const __grid_constant__ Params P) {
  extern __shared__ __align__(1024) uint8_t smem_raw[];
  constexpr uint32_t sbase = 1024;
  const uint32_t bars = sbase + OFF_BAR;
  const int warp = threadIdx.x >> 5, lane = threadIdx.x & 31;
#define BAR(i) (bars + 8 * (i))

  const int c1 = perm7(blockIdx.x, MAPA);
  const int ti1 = c1 >> 3, tg1 = c1 & 7;
  if (threadIdx.x == 0) {
    SCLKP(89);
    const CUtensorMap* wd = (tg1 < 4) ? &P.wdre : &P.wdim;
    if (TMPF) { prefetch_tmap(&P.xa); prefetch_tmap(wd); }
    for (int i = 0; i < EARLY; i++) mbar_init(BAR(B_FULL + i), 1);
    INIT_FENCE();
#pragma unroll 1
    for (int k = 0; k < EARLY; k++) {
      const uint32_t fb = BAR(B_FULL + k), s0 = 2 + 2 * k, s1 = k == 3 ? 0 : s0 + 1;
      mbar_expect_tx(fb, 32768);
      tma_ld2(sbase + s0 * SLOT, &P.xa, k * 64, ti1 * 128, fb);
      tma_ld2(sbase + s1 * SLOT, wd, k * 64, (tg1 & 3) * 128, fb);
    }
    SCLKP(88);
  }
  if (threadIdx.x == 32) {
    for (int i = EARLY; i < 11; i++) mbar_init(BAR(B_FULL + i), 1);
    for (int i = 0; i < NS; i++) mbar_init(BAR(B_EMPTY + i), 2);
    for (int i = 0; i < 2; i++) asm volatile("mbarrier.arrive.shared::cta.b64 _, [%0], 2;" ::"r"(BAR(B_EMPTY + i)) : "memory");
    INIT_FENCE();
  }
  if (threadIdx.x == 64) {
    mbar_init(BAR(B_STGA), S2 ? 128 : 256); mbar_init(BAR(B_STGB), 256); mbar_init(BAR(B_DONE), 2); mbar_init(BAR(B_KVISS), 1);
    if (S2) mbar_init(BAR(B_STGA1), 128);
    if (KV0) mbar_init(BAR(B_KV0), 256);
    if (S2) for (int i = 0; i < 16; i++) mbar_init(BAR(B_RDY + i), 1);
    mbar_init(BAR(B_KVFULL), 1); mbar_init(BAR(B_KVFULL + 1), 1);
    mbar_init(BAR(B_KVFREE), 2); mbar_init(BAR(B_KVFREE + 1), 2);
    mbar_init(BAR(B_WOFULL), 2); mbar_init(BAR(B_EPRDY), 1); mbar_init(BAR(B_XFREE), S2 ? 2 : 1); mbar_init(BAR(B_KVST), 1); mbar_init(BAR(B_WOLATE), 1);
    INIT_FENCE();
  }
  static_assert(!S2 && BS, "HLP");
  if (threadIdx.x == 96) {
    for (int i = 0; i < 8; i++) mbar_init(BAR(B_HLP + i), 4);
    INIT_FENCE();
  }
  __syncthreads();

  const uint32_t bid = blockIdx.x;
  const int c = perm7(bid, MAPB), c2 = perm7(bid, MAP2), c3 = perm7(bid, MAP3);
  const int ti = c >> 3, tg = c & 7;
  const int am = c2 >> 3, akq = (c2 >> 1) & 3, an = c2 & 1;
  const int rb = c3 >> 2, cn = c3 & 3;

  if (warp < 4) {
    asm volatile("setmaxnreg.dec.sync.aligned.u32 40;");
    if (warp == 0) {
      if (elect_one()) {
        STAMP(0);
        uint32_t slot = EARLY == 4 ? 1 : 2 + 2 * EARLY, eph = EARLY == 4 ? 0 : 1, dst = 0;
        SCLKP(86);
#define ACQ() mbar_wait(BAR(B_EMPTY + slot), eph); dst = sbase + slot * SLOT; if (++slot == NS) { slot = 0; eph ^= 1; }
        {
          const CUtensorMap* wd = (tg1 < 4) ? &P.wdre : &P.wdim;
PU1
          for (int k = EARLY; k < 8; k++) {
            const uint32_t fb = BAR(B_FULL + k);
            mbar_expect_tx(fb, 32768);
            ACQ() tma_ld2(dst, &P.xa, k * 64, ti1 * 128, fb);
            ACQ() tma_ld2(dst, wd, k * 64, (tg1 & 3) * 128, fb);
            if (k == EARLY) SCLKP(87);
            if (!EARLY && k == 2) SCLKP(88);
          }
        }
#undef ACQ
        uint32_t j = 0, fb = 0;
        eph = 1;
#define ACQ3(bytes) mbar_wait(BAR(B_EMPTY + 3 * j), eph); dst = sbase + j * (3 * SLOT); fb = BAR(B_FULL2 + j); \
                    if (++j == 3) { j = 0; eph ^= 1; }
PU1
        for (int k = 0; k < 8; k++) {
          if (k < 3) { mbar_wait(BAR(B_EMPTY + 3 * k + 1), 1); mbar_wait(BAR(B_EMPTY + 3 * k + 2), 1); }
          ACQ3()
          if (k == 2) STAMPB(30);
          if (k == 3) STAMPB(27);
          mbar_expect_tx(fb, 40960);
          tma_ld2(dst, &P.xb, k * 64, ti * 128, fb);
          tma_ld3(dst + SLOT, &P.wqkv, tg * 64, k * 64, 0, fb);
          tma_ld3(dst + 2 * SLOT, &P.wqkv, tg * 64, k * 64 + 32, 0, fb);
        }
        {
          const CUtensorMap* ws = (akq < 2) ? &P.wsre : &P.wsim;
          const int s0 = (akq & 1) * 1024, r0 = (akq >> 1) * 2048 + s0;
          {
            mbar_wait(BAR(B_EPRDY), 0);
            unsigned ep;
            asm volatile("ld.shared.u32 %0, [%1];" : "=r"(ep) : "r"(sbase + OFF_EP) : "memory");
            SCLKP(68);
            poll_ge(&g_cnt[(C_A1 + akq * 2 + an) * 32], ep * 16);
            fence_async_glb();
            STAMP(1);
            SCLKP(69);
          }
PU1
          for (int k = 0; k < 16; k++) {
            ACQ3()
            if (HOLD && k == HOLD) mbar_wait(BAR(B_KVISS), 0);
            SCLKP(70 + k);
            mbar_expect_tx(fb, 49152);
            tma_ld2(dst, ws, s0 + k * 64, am * 128, fb);
            if (!HOIST && k == 0) {
              mbar_wait(BAR(B_EPRDY), 0);
              unsigned ep;
              asm volatile("ld.shared.u32 %0, [%1];" : "=r"(ep) : "r"(sbase + OFF_EP) : "memory");
              poll_ge(&g_cnt[(C_A1 + akq * 2 + an) * 32], ep * 16);
              fence_async_glb();
              STAMP(1);
            }
            tma_ld3(dst + SLOT, &P.abld, 0, r0 + k * 64, an * 4, fb);
            tma_ld3(dst + 2 * SLOT, &P.abld, 0, r0 + k * 64 + 32, an * 4, fb);
          }
        }
        ACQ3()
        mbar_expect_tx(BAR(B_WOFULL), 3 * 16384);
        tma_ld3(dst, &P.wo, 0, 1 * 64, cn * 2, BAR(B_WOFULL));
        tma_ld3(dst + SLOT, &P.wo, 0, 2 * 64, cn * 2, BAR(B_WOFULL));
        tma_ld3(dst + 2 * SLOT, &P.wo, 0, 5 * 64, cn * 2, BAR(B_WOFULL));
        ACQ3()
        mbar_expect_tx(BAR(B_WOLATE), 3 * 16384);
        tma_ld3(dst, &P.wo, 0, 3 * 64, cn * 2, BAR(B_WOLATE));
        tma_ld3(dst + SLOT, &P.wo, 0, 6 * 64, cn * 2, BAR(B_WOLATE));
        tma_ld3(dst + 2 * SLOT, &P.wo, 0, 7 * 64, cn * 2, BAR(B_WOLATE));
#undef ACQ3
      }
    } else if (warp == 1) {
      if (elect_one()) {
        const unsigned ep = g_epoch[c] + 1;
        g_epoch[c] = ep;
        asm volatile("st.shared.u32 [%0], %1;" ::"r"(sbase + OFF_EP), "r"(ep) : "memory");
        mbar_arrive(BAR(B_EPRDY));
        mbar_wait(BAR(B_STGA), 0);
        {
          const int row = (tg1 >> 2) * 2048 + ti1 * 128, kq = (tg1 >> 2) * 2 + (ti1 >> 3);
          const int col0 = (tg1 & 2) * 128 + (((tg1 & 1) * 2 - kq - (TL == 2)) & 3) * 64, col1 = (tg1 & 2) * 128 + (((tg1 & 1) * 2 + 1 - kq - (TL == 2)) & 3) * 64;
          const uint32_t x = sbase + OFF_X;
#pragma unroll
          for (int i = 0; i < 32768 / (ABR * 128); i++) {
            const int r0 = (i * ABR) & 63, hb = (i * ABR) >> 6;
            tma_st2(&P.abst, x + i * ABR * 128, (hb & 1) ? col1 : col0, row + (hb >> 1) * 64 + r0);
            if (PACE > 0 && i + 1 < 32768 / (ABR * 128)) __nanosleep(PACE);
          }
        }
        bulk_commit();
        SCLKP(60);
        bulk_wait<0>();
        SCLKP(61);
        mbar_arrive(BAR(B_XFREE));
        red_release<FVA>(&g_cnt[(C_A1 + (tg1 >> 2) * 4 + (ti1 >> 3) * 2 + ((tg1 >> 1) & 1)) * 32]);
        STAMP(20);
        SCLKP(62);
        mbar_wait(BAR(B_STGB), 0);
        STAMP(21);
        SCLKP(63);
        unsigned* fl = &g_cnt[(C_KV + c) * 32];
PU1
        for (int h = KV0; h < 4; h++) {
          bulk_st(g_kv + (size_t)c * 2048 + h * 512, sbase + OFF_KV + h * 8192, 8192); bulk_commit();
          bulk_wait<0>();
          if (h == KV0) SCLKP(64);
          red_release<FV>(fl);
          if (h == KV0) STAMP(22);
          if (h == KV0) SCLKP(65);
        }
        mbar_arrive(BAR(B_KVST));
        STAMP(24);
#define SEND8K(dst, src) { \
          if (GAP == 0) bulk_st(dst, src, 8192); \
          else { \
            _Pragma("unroll 1") for (int i_ = 0; i_ < 8192 / SPC; i_++) { \
              _Pragma("unroll 1") for (int it_ = 0; it_ < 4096 && (int)((unsigned)clock() - tn_) < 0; it_++) { } \
              tn_ = (unsigned)clock() + GAP; \
              bulk_st((dst) + i_ * (SPC / 16), (src) + i_ * SPC, SPC); \
            } } }
#define OUT_HELPER(w) { \
          mbar_wait(BAR(B_HLP + (w)), 0); \
          unsigned tn_ = (unsigned)clock(); \
          uint4* pb = g_part + (size_t)((am * 2 + an) * 16 + akq) * 1024 + (w) * 512; \
          SEND8K(pb + ((akq + 1) & 3) * 4096, sbase + OFF_X + 16384 + (w) * 8192) \
          SEND8K(pb + ((akq + 2) & 3) * 4096, sbase + OFF_KV + 16384 + (w) * 8192) \
          if (TL == 2) { bulk_commit(); mbar_wait(BAR(B_HLP + 6 + (w)), 0); } \
          SEND8K(pb + ((akq + 3) & 3) * 4096, sbase + OFF_Q + (w) * 8192) \
          bulk_commit(); \
          mbar_wait(BAR(B_HLP + 2 + (w)), 0); \
          tma_st2(&P.out, sbase + (w) * 8192, 512 + cn * 128 + (w) * 64, rb * 64); \
          bulk_commit(); \
          mbar_wait(BAR(B_HLP + 4 + (w)), 0); \
          tma_st2(&P.out, sbase + 16384 + (w) * 8192, an * 256 + akq * 64, am * 128 + (w) * 64); \
          bulk_commit(); \
          bulk_wait_read(); }
        OUT_HELPER(0)
      }
    } else if (warp == 3) {
      mbar_wait(BAR(B_EPRDY), 0);
      unsigned ep;
      asm volatile("ld.shared.u32 %0, [%1];" : "=r"(ep) : "r"(sbase + OFF_EP) : "memory");
      if (elect_one()) {
        mbar_wait(BAR(B_STGB), 0);
PU1
        for (int u = KV0; u < 4; u++) {
          const uint32_t fbk = BAR(B_KVFULL + (u & 1)), x = sbase + OFF_X + (u & 1) * 16384;
          if (ti >= 1) poll2_ge(&g_cnt[(C_KV + c - 8) * 32], &g_cnt[(C_KV + (ti >= 2 ? c - 16 : c - 8)) * 32], (ep - 1) * (4 - KV0) + u + 1 - KV0);
          if (u == KV0) SCLKP(66);
          if (u == KV0) { mbar_wait(BAR(B_XFREE), 0); STAMP(23); }
          fence_async_glb();
          if (u >= 2) mbar_wait(BAR(B_KVFREE + (u & 1)), 0);
          mbar_expect_tx(fbk, 16384);
          bulk_ld(x, ti >= 2 ? g_kv + (size_t)(c - 16) * 2048 + u * 512 : g_zero, 8192, fbk);
          bulk_ld(x + 8192, ti >= 1 ? g_kv + (size_t)(c - 8) * 2048 + u * 512 : g_zero, 8192, fbk);
          if (HOLD && u == KV0) mbar_arrive(BAR(B_KVISS));
          if (u == KV0) SCLKP(67);
        }
        mbar_wait(BAR(B_KVFREE), 1);
        mbar_wait(BAR(B_KVST), 0);
        mbar_expect_tx(BAR(B_WOFULL), 2 * 16384);
        tma_ld3(sbase + OFF_X, &P.wo, 0, 0 * 64, cn * 2, BAR(B_WOFULL));
        tma_ld3(sbase + OFF_KV, &P.wo, 0, 4 * 64, cn * 2, BAR(B_WOFULL));
        OUT_HELPER(1)
      }
    } else if (warp == 2) {
      if (elect_one()) {
        if (smem_u32(smem_raw) != 1024) __trap();
        prefetch_tmap(&P.xb); prefetch_tmap(&P.wqkv); prefetch_tmap(&P.abst); prefetch_tmap(&P.abld);
        prefetch_tmap(akq < 2 ? &P.wsre : &P.wsim); prefetch_tmap(&P.wo); prefetch_tmap(&P.out);
        watchdog(BAR(B_DONE));
      }
    }
  } else {
    asm volatile("setmaxnreg.inc.sync.aligned.u32 232;");
    const int wg = __shfl_sync(0xffffffffu, (warp >> 2) - 1, 0), wq = __shfl_sync(0xffffffffu, warp & 3, 0);
    const bool lead = (threadIdx.x & 127) == 0;
    constexpr uint32_t dbase = 1024 >> 4;
#define DLO(off, lbo16) (dbase + ((off) >> 4) + ((lbo16) << 16))
#define REL(s) mbar_arrive_if(BAR(B_EMPTY + (s)), lead)
    const uint32_t dA = DLO(0, 1) + wg * 512;

    SCLKC(96); SGT(95);
    {
      float acc[64];
#pragma unroll
      for (int k = 0; k < 8; k++) {
        const int sa = (2 + 2 * k) % NS, sb = (3 + 2 * k) % NS;
        mbar_wait(BAR(B_FULL + k), 0);
        if (k == 0 && threadIdx.x == 128) STAMP(2);
        if (k == 0) SCLKC(97);
        if (k == 7 && threadIdx.x == 128) STAMP(3);
        const uint64_t da = mkd(dA + sa * 1024, HI128), db = mkd(DLO(sb * SLOT, 1), HI128);
        wgmma_fence();
#pragma unroll
        for (int kk = 0; kk < 4; kk++) wgmma_ss_n128(acc, da + 2 * kk, db + 2 * kk, (k | kk) != 0);
        wgmma_commit();
        if (k > 0) { wgmma_wait<1>(); REL((2 * k) % NS); REL((1 + 2 * k) % NS); }
      }
      wgmma_wait<0>();
      reg_fence(acc);
      if (threadIdx.x == 128) STAMP(25);
      SCLKC(98);
      REL(16 % NS); REL(17 % NS);
      const uint32_t sgn = tg1 < 4 ? 0u : 0x80008000u;
      stage64(sbase + OFF_X + wg * 16384, acc, wq, lane, sgn);
      stage64(sbase + OFF_X + wg * 16384 + 8192, acc + 32, wq, lane, sgn);
      fence_async_smem();
      mbar_arrive(BAR((S2 && wg) ? B_STGA1 : B_STGA));
    }
    if (threadIdx.x == 128) STAMP(4);
    SCLKC(99);
#define WAITQ(q) mbar_wait(BAR(B_FULL2 + (q) % 3), ((q) / 3) & 1)
#define RELQ(q) REL(3 * ((q) % 3))
    {
      float acc[96];
#pragma unroll
      for (int k = 0; k < 8; k++) {
        WAITQ(k);
        if (k == 0 && threadIdx.x == 128) STAMPB(17);
        if (k == 3 && threadIdx.x == 128) STAMPB(18);
        if (k == 1 && threadIdx.x == 128) STAMPB(28);
        if (k == 2 && threadIdx.x == 128) STAMPB(29);
        if (k == 7 && threadIdx.x == 128) STAMPB(19);
        const int so = (k % 3) * 3 * SLOT;
        const uint64_t da = mkd(dA + (so >> 4), HI128), db0 = mkd(DLO(so + SLOT, 256), HI128), db1 = mkd(DLO(so + 2 * SLOT, 256), HI128);
        wgmma_fence();
        wgmma_ss_n192(acc, da, db0, k != 0);
        wgmma_ss_n192(acc, da + 2, db0 + 128, 1);
        wgmma_ss_n192(acc, da + 4, db1, 1);
        wgmma_ss_n192(acc, da + 6, db1 + 128, 1);
        wgmma_commit();
        if (k > 0) { wgmma_wait<1>(); RELQ(k - 1); }
      }
      wgmma_wait<0>();
      reg_fence(acc);
      if (threadIdx.x == 128) STAMP(26);
      SCLKC(104);
      RELQ(7);
      stage64(sbase + OFF_Q + wg * 8192, acc, wq, lane);
      const int row = wg * 64 + wq * 16 + (lane & 7) + ((lane >> 3) & 1) * 8;
      const uint32_t rbk = sbase + OFF_KV + row * 32 + ((((lane >> 4) ^ (row >> 2)) & 1) << 4);
#pragma unroll
      for (int j = 0; j < 8; j++) {
        const float* a = acc + 32 + 8 * j;
        stsm4(rbk + (j & 3) * 8192 + (j >> 2) * 4096, pack_bf16(a[0], a[1]), pack_bf16(a[2], a[3]), pack_bf16(a[4], a[5]), pack_bf16(a[6], a[7]));
      }
      fence_async_smem();
      mbar_arrive(BAR(B_STGB));
    }
    if (threadIdx.x == 128) STAMP(5);
    SCLKC(105);
    float keep[32];
    uint32_t tag, badmask = 0;
    uint32_t af[16][4], pp[48];
    const int tid = threadIdx.x & 127;
    mbar_wait(BAR(B_EPRDY), 0);
    asm volatile("ld.shared.u32 %0, [%1];" : "=r"(tag) : "r"(sbase + OFF_EP) : "memory");
    tag &= 1;
    {
      float acc[128];
      uint32_t wA = wg * 512;
#define BIG2(hs) { const int so_ = ((8 + ((hs) >> 1)) % 3) * 3 * SLOT; \
          const uint64_t da_ = mkd(DLO(so_, 1) + ((hs) & 1) * 4 + wA, HI128), db_ = mkd(DLO(so_ + SLOT * (1 + ((hs) & 1)), 256), HI128); \
          wgmma_ss_n256(acc, da_, db_, (hs) != 0); \
          wgmma_ss_n256(acc, da_ + 2, db_ + 128, 1); }
      static_assert(HS0 % 2 == 0 && HS0 >= 2 && HS0 <= 12, "HS0");
#pragma unroll
      for (int k = 0; k < HS0 / 2; k++) {
        WAITQ(8 + k);
        wgmma_fence();
        BIG2(2 * k) BIG2(2 * k + 1)
        wgmma_commit();
        if (k > 0) { wgmma_wait<1>(); RELQ(8 + k - 1); }
      }
      {
        float sD[8], sT[8], sF[16], oa[8];
        uint32_t pk[16], qf[4];
        float aD0 = 0.f, aD1 = 0.f, aT0 = 0.f, aT1 = 0.f, l0 = 0.f, l1 = 0.f;
        const float CS = 0.25f * 1.4426950408889634f;
        const float BIG = 1e30f;
        const uint32_t own0 = DLO(OFF_KV, 1), x0 = DLO(OFF_X, 1);
        const int lim = 3 - 2 * ti - wg;
        float nbT = (lim >= 0) ? -BIG : 0.f;
        asm volatile("" : "+f"(nbT));
        uint32_t wD = wg * 128, wF = wg * 384, wC = wg;
        uint32_t vD = 0, vT = 0, vF = 0;
        const int zz = blockIdx.x >> 10;
        uint32_t MD = (2 * (lane & 3) <= (lane >> 2) ? 0xffffu : 0u) | (2 * (lane & 3) + 1 <= (lane >> 2) ? 0xffff0000u : 0u);
        asm volatile("" : "+r"(MD));
        uint32_t qa;
        {
          const int row = wg * 64 + wq * 16 + (lane & 7) + ((lane >> 3) & 1) * 8;
          qa = sbase + OFF_Q + row * 128 + (((lane >> 4) ^ (row & 7)) << 4);
        }
        uint4* op = g_o + (size_t)((2 * ti + wg) * 32 + 4 * tg) * 128 + tid;
        if (threadIdx.x == 128) STAMP(11);
        SCLK(100);
        WAITQ(8 + HS0 / 2);
        mbar_wait(BAR(B_STGB), 0);
        ldsm4(qf, qa);
        mbar_wait(BAR(KV0 ? B_KV0 : B_KVFULL), 0);
        if (threadIdx.x == 128) STAMP(12);
        SCLK(101);
#define FIN_PRE() \
          float a_ = l0 + __shfl_xor_sync(~0u, l0, 1), b_ = l1 + __shfl_xor_sync(~0u, l1, 1); \
          a_ += __shfl_xor_sync(~0u, a_, 2); b_ += __shfl_xor_sync(~0u, b_, 2); \
          const float ab_ = a_ + b_; \
          a_ = rcp(a_); b_ = rcp(b_);
#define FIN_PRE_V() \
          a_ = l0 + __shfl_xor_sync(~0u, l0, 1); b_ = l1 + __shfl_xor_sync(~0u, l1, 1); \
          a_ += __shfl_xor_sync(~0u, a_, 2); b_ += __shfl_xor_sync(~0u, b_, 2); \
          ab_ = a_ + b_; a_ = rcp(a_); b_ = rcp(b_);
#define FIN_POST(uu, valid) { \
          const float z_ = fmaf(((oa[0] + oa[1]) + (oa[2] + oa[3])) + ((oa[4] + oa[5]) + (oa[6] + oa[7])), 0.f, ab_); \
          const bool bad_ = __any_sync(~0u, !(z_ <= 1.2676506e30f)); \
          st_pkt_if(op + (uu) * 128, pack_bf16(oa[0] * a_, oa[1] * a_), pack_bf16(oa[2] * b_, oa[3] * b_), pack_bf16(oa[4] * a_, oa[5] * a_), \
                    pack_bf16(oa[6] * b_, oa[7] * b_), tag, (valid) && !bad_); \
          badmask |= ((valid) && bad_) ? 1u << (uu) : 0u; }
#define KVPAR(u) (KV0 ? ((u) == 3) : ((u) >= 2))
#define PV4(first) \
          wgmma_rs_n16(oa, pk[0], pk[1], pk[2], pk[3], mkd(vD, HI32), first); \
          wgmma_rs_n16(oa, pk[4], pk[5], pk[6], pk[7], mkd(vT, HI32), 1); \
          wgmma_rs_n16(oa, pk[8], pk[9], pk[10], pk[11], mkd(vF, HI32), 1); \
          wgmma_rs_n16(oa, pk[12], pk[13], pk[14], pk[15], mkd(vF + 32, HI32), 1);
#define EXP4(dst, s, i, a0_, a1_) { \
          s[i] = ex2(fmaf(s[i], CS, a0_)); s[(i) + 1] = ex2(fmaf(s[(i) + 1], CS, a0_)); \
          s[(i) + 2] = ex2(fmaf(s[(i) + 2], CS, a1_)); s[(i) + 3] = ex2(fmaf(s[(i) + 3], CS, a1_)); \
          l0 += s[i] + s[(i) + 1]; l1 += s[(i) + 2] + s[(i) + 3]; \
          pk[dst] = pack_bf16(s[i], s[(i) + 1]); pk[(dst) + 1] = pack_bf16(s[(i) + 2], s[(i) + 3]); }
        uint32_t t = 2 * ((8 + HS0 / 2) % 3), ph = ((8 + HS0 / 2) / 3) & 1;
#pragma unroll
        for (int i = 0; i < 16; i++) pk[i] = 0;
#pragma unroll
        for (int i = 0; i < 8; i++) oa[i] = 0.f;
        vD = vT = vF = own0 + 256;
#pragma unroll
        for (int u = 0; u < 4; u++)
#pragma unroll
        for (int b = 0; b < 5; b++) {
          asm volatile("" : "+r"(wD), "+r"(wF), "+r"(wA));
          const uint32_t xo = x0 + (u & 1) * 1024;
          uint32_t kFc = 0;
          if (b == 4) { asm volatile("" : "+r"(wC)); kFc = xo + 640 + wC * (own0 + 512 * u - xo - 640); }
          const uint32_t cD = b < 4 ? own0 + 512 * u + 32 * b + wD : kFc, cT = b < 4 ? xo + 32 * b + wD : kFc + 32;
          const uint32_t cF = b < 2 ? xo + 128 + 64 * b + wF : b < 4 ? xo + 512 + 64 * (b - 2) + wD : kFc + 64;
          const uint32_t tn = t == 5 ? 0 : t + 1, phn = ph ^ (t == 5);
          const uint64_t da_ = mkd(DLO(0, 1) + (t >> 1) * 3072 + (t & 1) * 4 + wA, HI128), db_ = mkd(DLO(SLOT, 256) + (t + (t >> 1)) * 1024, HI128);
          wgmma_fence();
          PV4(b != 1)
          wgmma_rs_n16k(sD, qf[0], qf[1], qf[2], qf[3], mkd(cD, HI32), zz);
          wgmma_rs_n16k(sT, qf[0], qf[1], qf[2], qf[3], mkd(cT, HI32), zz);
          wgmma_rs_n32k(sF, qf[0], qf[1], qf[2], qf[3], mkd(cF, HI32), zz);
          wgmma_commit();
          wgmma_ss_n256(acc, da_, db_, 1);
          wgmma_ss_n256(acc, da_ + 2, db_ + 128, 1);
          wgmma_commit();
          vD = cD + 256; vT = cT + 256; vF = cF + 256;
          const uint32_t fbn = BAR(B_FULL2) + (tn >> 1) * 8, kbn = BAR(B_KVFULL) + ((u + 1) & 1) * 8;
          const uint32_t okF = mbar_test(fbn, phn);
          uint32_t okK = 1;
          if (b == 4) okK = mbar_test(kbn, KVPAR(u + 1));
          float a_ = 0.f, b_ = 0.f, ab_ = 0.f;
          if (FINS && b == 0) { FIN_PRE_V() }
          SCLKF(3 * (5 * u + b));
          wgmma_wait<1>();
          SCLKF(3 * (5 * u + b) + 1);
          reg_fence(sD); reg_fence(sT); reg_fence(sF);
          reg_fence(oa);
          mbar_arrive_if(BAR(B_EMPTY) + (t == 0 ? 2 : (t >> 1) - 1) * 24, lead && !(t & 1));
          if (b == 4) ldsm4(qf, qa ^ ((u + 1) << 5));
          const bool Pb = b < 4 && wq >= b, Pc = b < 4 && wq > b;
          const uint32_t Ma = Pc ? 0xffffffffu : (Pb ? MD : 0u);
          const bool P0 = Ma & 1u, P1 = (int)Ma < 0;
          const float nbF = ((b >> 1) < lim) ? -BIG : 0.f;
          if (b == 0) {
            if (!FINS) { FIN_PRE_V() }
            FIN_POST(u - 1, u > 0)
            mbar_arrive_if(BAR(B_KVFREE) + ((u + 1) & 1) * 8, lead && u > 0);
            float* v = sD;
            v[0] = P0 ? v[0] * CS : fmaf(sT[0], CS, nbT); v[1] = P1 ? v[1] * CS : fmaf(sT[1], CS, nbT);
            v[2] = v[2] * CS; v[3] = v[3] * CS;
            v[4] = Pc ? v[4] * CS : fmaf(sT[4], CS, nbT); v[5] = Pc ? v[5] * CS : fmaf(sT[5], CS, nbT);
            v[6] = P0 ? v[6] * CS : fmaf(sT[6], CS, nbT); v[7] = P1 ? v[7] * CS : fmaf(sT[7], CS, nbT);
            float x0_ = fmaxf(fmaxf(v[0], v[1]), fmaxf(v[4], v[5])), x1_ = fmaxf(fmaxf(v[2], v[3]), fmaxf(v[6], v[7]));
            x0_ = fmaxf(x0_, __shfl_xor_sync(~0u, x0_, 1)); x1_ = fmaxf(x1_, __shfl_xor_sync(~0u, x1_, 1));
            x0_ = fmaxf(x0_, __shfl_xor_sync(~0u, x0_, 2)); x1_ = fmaxf(x1_, __shfl_xor_sync(~0u, x1_, 2));
            aD0 = -60.f - x0_; aD1 = -60.f - x1_;
            aT0 = aD0 + nbT; aT1 = aD1 + nbT;
            asm volatile("" : "+f"(aT0), "+f"(aT1));
            v[0] = ex2(v[0] + aD0); v[1] = ex2(v[1] + aD0); v[2] = ex2(v[2] + aD1); v[3] = ex2(v[3] + aD1);
            v[4] = ex2(v[4] + aD0); v[5] = ex2(v[5] + aD0); v[6] = ex2(v[6] + aD1); v[7] = ex2(v[7] + aD1);
            l0 = (v[0] + v[1]) + (v[4] + v[5]); l1 = (v[2] + v[3]) + (v[6] + v[7]);
            const uint32_t m0 = pack_bf16(v[0], v[1]), m2 = pack_bf16(v[4], v[5]), m3 = pack_bf16(v[6], v[7]);
            pk[0] = m0 & Ma; pk[1] = pack_bf16(v[2], v[3]); pk[2] = Pc ? m2 : 0u; pk[3] = m3 & Ma;
            pk[4] = m0 & ~Ma; pk[5] = 0; pk[6] = Pc ? 0u : m2; pk[7] = m3 & ~Ma;
          } else if (b < 4) {
            float* e = sD;
            e[0] = ex2(P0 ? fmaf(e[0], CS, aD0) : fmaf(sT[0], CS, aT0)); e[1] = ex2(P1 ? fmaf(e[1], CS, aD0) : fmaf(sT[1], CS, aT0));
            e[2] = ex2(Pb ? fmaf(e[2], CS, aD1) : fmaf(sT[2], CS, aT1)); e[3] = ex2(Pb ? fmaf(e[3], CS, aD1) : fmaf(sT[3], CS, aT1));
            e[4] = ex2(Pc ? fmaf(e[4], CS, aD0) : fmaf(sT[4], CS, aT0)); e[5] = ex2(Pc ? fmaf(e[5], CS, aD0) : fmaf(sT[5], CS, aT0));
            e[6] = ex2(P0 ? fmaf(e[6], CS, aD1) : fmaf(sT[6], CS, aT1)); e[7] = ex2(P1 ? fmaf(e[7], CS, aD1) : fmaf(sT[7], CS, aT1));
            l0 += (e[0] + e[1]) + (e[4] + e[5]); l1 += (e[2] + e[3]) + (e[6] + e[7]);
            const uint32_t m0 = pack_bf16(e[0], e[1]), m1 = pack_bf16(e[2], e[3]), m2 = pack_bf16(e[4], e[5]), m3 = pack_bf16(e[6], e[7]);
            pk[0] = m0 & Ma; pk[1] = Pb ? m1 : 0u; pk[2] = Pc ? m2 : 0u; pk[3] = m3 & Ma;
            pk[4] = m0 & ~Ma; pk[5] = Pb ? 0u : m1; pk[6] = Pc ? 0u : m2; pk[7] = m3 & ~Ma;
          }
          const float aF0 = aD0 + nbF, aF1 = aD1 + nbF;
          if (b == 4) {
            EXP4(0, sD, 0, aF0, aF1) EXP4(2, sD, 4, aF0, aF1)
            EXP4(4, sT, 0, aF0, aF1) EXP4(6, sT, 4, aF0, aF1)
          }
          EXP4(8, sF, 0, aF0, aF1) EXP4(10, sF, 4, aF0, aF1) EXP4(12, sF, 8, aF0, aF1) EXP4(14, sF, 12, aF0, aF1)
          SCLKF(3 * (5 * u + b) + 2);
          if (b == 4) SCLKC(106 + u);
          if (b == 4 && threadIdx.x == 128) STAMP(13 + u);
          mbar_wait_if(okF, fbn, phn);
          if (b == 4) mbar_wait_if(okK, kbn, KVPAR(u + 1));
          t = tn; ph = phn;
        }
        static_assert(HS0 == 8 && BS && HLP, "TL");
        float (&accL)[64] = *reinterpret_cast<float (*)[64]>(acc);
        float hi[64];
#define HALF2(a_, hs, off, first) { const int so_ = ((8 + ((hs) >> 1)) % 3) * 3 * SLOT; \
          const uint64_t da_ = mkd(DLO(so_, 1) + ((hs) & 1) * 4 + wA, HI128), db_ = mkd(DLO(so_ + SLOT * (1 + ((hs) & 1)), 256) + (off), HI128); \
          wgmma_ss_n128t(a_, da_, db_, !(first)); \
          wgmma_ss_n128t(a_, da_ + 2, db_ + 128, 1); }
        wgmma_fence();
        PV4(1)
        wgmma_commit();
        BIG2(28)
        wgmma_commit();
        FIN_PRE()
        wgmma_wait<1>();
        reg_fence(oa);
        RELQ(21);
        FIN_POST(3, true)
        bar_arrive(4 + wg, 256);
        wgmma_fence();
        BIG2(29)
        wgmma_commit();
        if (AFE == 1) {
          const uint4* oin = g_o + (size_t)(rb * 32 + 16 * wg) * 128 + tid;
#pragma unroll
          for (int j = 0; j < 4; j++)
#pragma unroll
            for (int h = 0; h < 3; h++) ld_pkt(oin + (4 * j + h) * 128, af[4 * h + j]);
        }
        WAITQ(23);
        wgmma_wait<0>();
        reg_fence(acc);
        RELQ(22);
        wgmma_fence();
#define TLX 3
        if (TLX == 4) {
          const float one = __uint_as_float(0x3f800000u + gridDim.x - 128u);
#pragma unroll
          for (int i = 0; i < 64; i++) { hi[i] = acc[64 + i] * one; }
          reg_fence(hi);
          wgmma_fence();
        }
        if (TLX != 2) { HALF2(accL, 30, 0, 0) HALF2(accL, 31, 0, 0) }
        wgmma_commit();
        if (TLX == 3) {
          const float one = __uint_as_float(0x3f800000u + gridDim.x - 128u);
#pragma unroll
          for (int i = 0; i < 64; i++) { hi[i] = acc[64 + i] * one; }
          reg_fence(hi);
          wgmma_fence();
        }
        if (TLX >= 3) { HALF2(hi, 30, 512, 0) HALF2(hi, 31, 512, 0) }
        else if (TLX != 1) { HALF2(hi, 30, 512, 1) HALF2(hi, 31, 512, 0) }
        else { _Pragma("unroll") for (int i = 0; i < 64; i++) hi[i] = 0.f; }
        wgmma_commit();
        bar_sync(4 + (wg ^ 1), 256);
        mbar_wait(BAR(B_KVST), 0);
        wgmma_wait<1>();
        reg_fence(accL);
        if (PKP == 4) SCLKC(110);
        {
          const uint32_t sg[2] = {sbase + OFF_X + 16384 + wg * 8192, sbase + OFF_KV + 16384 + wg * 8192};
#pragma unroll
          for (int n = 0; n < 8; n++) {
            const float* a = acc + 8 * n;
            const uint32_t a0 = tag_pkt(pack_bf16(a[0], a[1]), tag);
            asm volatile("st.shared.v4.u32 [%0], {%1,%2,%3,%4};" ::"r"(sg[n >> 2] + wq * 2048 + (n & 3) * 512 + lane * 16), "r"(a0), "r"(pack_bf16(a[2], a[3])),
                         "r"(pack_bf16(a[4], a[5])), "r"(pack_bf16(a[6], a[7])) : "memory");
          }
          const uint4* oin = g_o + (size_t)(rb * 32 + 16 * wg) * 128 + tid;
          if (AFE == 2) {
#pragma unroll
            for (int j = 0; j < 4; j++)
#pragma unroll
              for (int h = 0; h < 3; h++) ld_pkt(oin + (4 * j + h) * 128, af[4 * h + j]);
          }
          fence_async_smem();
          __syncwarp();
          mbar_arrive_if(BAR(B_HLP) + wg * 8, lane == 0);
          if (AFE == 3) {
#pragma unroll
            for (int j = 0; j < 4; j++)
#pragma unroll
              for (int h = 0; h < 3; h++) ld_pkt(oin + (4 * j + h) * 128, af[4 * h + j]);
          }
        }
        if (PKP == 5) SCLKC(110);
        if (PKP == 7) { uint32_t v_; asm volatile("ld.volatile.shared.u32 %0, [%1];" : "=r"(v_) : "r"(sbase + OFF_EP) : "memory"); if (v_ == 0xfffffff0u) __trap(); SCLKC(110); }
        wgmma_wait<0>();
        reg_fence(hi);
#pragma unroll
        for (int i = 0; i < 32; i++) keep[i] = TLX >= 3 ? hi[32 + i] : acc[96 + i] + hi[32 + i];
#pragma unroll
        for (int i = 0; i < 16; i++) { pp[32 + i] = TLX >= 3 ? pack_bf16(hi[2 * i], hi[2 * i + 1]) : pack_bf16(acc[64 + 2 * i] + hi[2 * i], acc[65 + 2 * i] + hi[2 * i + 1]); asm volatile("" : "+r"(pp[32 + i])); }
      }
      if (threadIdx.x == 128) STAMP(6);
      SCLK(102);
      if (EXPB == 2 ? false : badmask != 0) {
        redo_units(badmask, tag, sbase, tid, wg, ti, tg);
      }
    }
    if (threadIdx.x == 128) STAMP(7);
    if (PKP == 0) SCLKC(110);
    float outb[32];
    uint32_t pq[12][4];
    constexpr int ISTR = BS ? 32 : 256;
    const uint4* pin = g_part + (size_t)((am * 2 + an) * 16 + akq * 4) * 1024 + (BS ? wg * 512 + wq * 128 + lane : wg * 128 + tid);
    {
      float acc[64];
      const uint4* oin = g_o + (size_t)(rb * 32 + 16 * wg) * 128 + tid;
      uint32_t wd[4];
      wd[0] = wg ? DLO(OFF_KV, 512) : DLO(OFF_X, 512);
      wd[1] = wg ? DLO(2 * SLOT, 512) : DLO(0, 512);
      wd[2] = wg ? DLO(4 * SLOT, 512) : DLO(SLOT, 512);
      wd[3] = wg ? DLO(5 * SLOT, 512) : DLO(3 * SLOT, 512);
      uint4* pbase = g_part + (size_t)((am * 2 + an) * 16 + akq) * 1024 + wg * 128 + tid;
      uint4* pd[3];
#pragma unroll
      for (int p = 0; p < 3; p++) pd[p] = pbase + ((akq + p + 1) & 3) * 4096;
#define SEND(n) st_pkt(pd[(n) >> 2] + ((n) & 3) * 256, pp[4 * (n)], pp[4 * (n) + 1], pp[4 * (n) + 2], pp[4 * (n) + 3], tag)
#define AFCHK() { \
        RETRY_LOOP { \
          uint32_t bad = 0; \
          _Pragma("unroll") for (int i = 0; i < 12; i++) bad |= af[i][0] ^ tag; \
          if (!__any_sync(0xffffffffu, bad & 1)) { DBGIT(0, it); break; } \
          _Pragma("unroll") for (int h = 0; h < 3; h++) \
            _Pragma("unroll") for (int j = 0; j < 4; j++) re_pkt(oin + (4 * j + h) * 128, af[4 * h + j], tag); \
        } \
        _Pragma("unroll") for (int i = 0; i < 12; i++) { if (!NOMASK) { af[i][0] &= ~1u; asm volatile("" : "+r"(af[i][0])); } } }
      if (TL != 2) {
        bar_sync(4 + (wg ^ 1), 256);
        mbar_wait(BAR(B_KVST), 0);
      }
      if (PKP == 1) SCLKC(110);
      if (AF3 == -1) {
#pragma unroll
        for (int jj = 0; jj < 4; jj++) ld_pkt(oin + (4 * jj + 3) * 128, af[12 + jj]);
      }
      {
        const uint32_t sg[3] = {sbase + OFF_X + 16384 + wg * 8192, sbase + OFF_KV + 16384 + wg * 8192, sbase + OFF_Q + wg * 8192};
#pragma unroll
        for (int n = TL == 2 ? 8 : 0; n < 12; n++) {
          const uint32_t a0 = tag_pkt(pp[4 * n], tag);
          asm volatile("st.shared.v4.u32 [%0], {%1,%2,%3,%4};" ::"r"(sg[n >> 2] + wq * 2048 + (n & 3) * 512 + lane * 16), "r"(a0), "r"(pp[4 * n + 1]),
                       "r"(pp[4 * n + 2]), "r"(pp[4 * n + 3]) : "memory");
        }
        if (PKP == 2) SCLKC(110);
        fence_async_smem();
        if (PKP == 3) SCLKC(110);
        if (PKP == 6) { uint32_t v_; asm volatile("ld.volatile.shared.u32 %0, [%1];" : "=r"(v_) : "r"(sbase + OFF_EP) : "memory"); if (v_ == 0xfffffff0u) __trap(); SCLKC(110); }
        if (AF3 == -4) AFCHK()
        if (AF3 == -3 || AF3 == -4) {
#pragma unroll
          for (int jj = 0; jj < 4; jj++) {
            if (RP & 4) { af[12 + jj][0] = af[12 + jj][1] = af[12 + jj][2] = af[12 + jj][3] = 0; ldt_pkt(oin + (4 * jj + 3) * 128, af[12 + jj]); }
            else ld_pkt(oin + (4 * jj + 3) * 128, af[12 + jj]);
          }
        }
        __syncwarp();
        mbar_arrive_if(BAR(B_HLP + (TL == 2 ? 6 : 0)) + wg * 8, lane == 0);
      }
      if (!(BS && AF3 == -4)) AFCHK()
      STAMPT(17);
      SCLKC(111);
      mbar_wait(BAR(B_WOFULL), 0);
      STAMPT(28);
      SCLKC(112);
      wgmma_fence();
#pragma unroll
      for (int j = 0; j < 4; j++) {
        if (j >= 2 && wg == (j == 2)) mbar_wait(BAR(B_WOLATE), 0);
#pragma unroll
        for (int h = 0; h < 3; h++) {
          uint32_t* a = af[4 * h + j];
          wgmma_rs_n128(acc, a[0], a[1], a[2], a[3], mkd(wd[j] + 128 * h, HI128), (h | j) != 0);
        }
#pragma unroll
        for (int n = ST0 + STR * j; n < ST0 + STR * j + STR; n++)
          if (n < 12 && !BS) SEND(n);
        if (j == AF3) {
#pragma unroll
          for (int jj = 0; jj < 4; jj++) ld_pkt(oin + (4 * jj + 3) * 128, af[12 + jj]);
        }
      }
      wgmma_commit();
      STAMPT(29);
      SCLKC(113);
      {
        RETRY_LOOP {
          uint32_t bad = 0;
#pragma unroll
          for (int i = 12; i < 16; i++) bad |= af[i][0] ^ tag;
          if (!__any_sync(0xffffffffu, bad & 1)) { DBGIT(1, it); break; }
#pragma unroll
          for (int j = 0; j < 4; j++) { if (RP & 8) ldt_pkt(oin + (4 * j + 3) * 128, af[12 + j]); else if (RP & 1) ld_pkt(oin + (4 * j + 3) * 128, af[12 + j]); else re_pkt(oin + (4 * j + 3) * 128, af[12 + j], tag); }
        }
      }
#pragma unroll
      for (int i = 12; i < 16; i++) { if (!NOMASK) { af[i][0] &= ~1u; asm volatile("" : "+r"(af[i][0])); } }
      STAMPT(18);
      SCLKC(114);
      wgmma_fence();
#pragma unroll
      for (int j = 0; j < 4; j++) {
        uint32_t* a = af[12 + j];
        wgmma_rs_n128(acc, a[0], a[1], a[2], a[3], mkd(wd[j] + 128 * 3, HI128), 1);
      }
      wgmma_commit();
      wgmma_wait<0>();
      reg_fence(acc);
      if (threadIdx.x == 128) STAMP(8);
      SCLKC(115);
#define PQLD() { _Pragma("unroll") for (int s = 0; s < 3; s++) { const int src = (akq + 3 - s) & 3; \
        _Pragma("unroll") for (int i = 0; i < 4; i++) ld_pkt(pin + src * 1024 + i * ISTR, pq[4 * s + i]); } }
      const uint32_t xw = sbase + (wg ? OFF_KV : OFF_X) + tid * 16, xr = sbase + (wg ? OFF_X : OFF_KV) + tid * 16;
      if (SWP || wg == 0) {
#pragma unroll
        for (int i = 0; i < 8; i++)
          asm volatile("st.shared.v4.f32 [%0], {%1,%2,%3,%4};" ::"r"(xw + i * 2048), "f"(acc[32 + 4 * i]), "f"(acc[33 + 4 * i]), "f"(acc[34 + 4 * i]), "f"(acc[35 + 4 * i]) : "memory");
#pragma unroll
        for (int i = 0; i < 32; i++) outb[i] = acc[i];
      } else {
#pragma unroll
        for (int i = 0; i < 8; i++)
          asm volatile("st.shared.v4.f32 [%0], {%1,%2,%3,%4};" ::"r"(xw + i * 2048), "f"(acc[4 * i]), "f"(acc[1 + 4 * i]), "f"(acc[2 + 4 * i]), "f"(acc[3 + 4 * i]) : "memory");
#pragma unroll
        for (int i = 0; i < 32; i++) outb[i] = acc[32 + i];
      }
      bar_sync(1, 256);
      STAMPT(19);
      SCLKC(116);
#pragma unroll
      for (int i = 0; i < 8; i++) {
        float v0, v1, v2, v3;
        asm volatile("ld.shared.v4.f32 {%0,%1,%2,%3}, [%4];" : "=f"(v0), "=f"(v1), "=f"(v2), "=f"(v3) : "r"(xr + i * 2048) : "memory");
        outb[4 * i] += v0; outb[4 * i + 1] += v1; outb[4 * i + 2] += v2; outb[4 * i + 3] += v3;
      }
      stage64(sbase + wg * 8192, outb, wq, lane);
      fence_async_smem();
      __syncwarp();
      mbar_arrive_if(BAR(B_HLP + 2) + wg * 8, lane == 0);
      PQLD()
      if (threadIdx.x == 128) STAMP(9);
      SCLKC(117);
      {
        RETRY_LOOP {
          uint32_t bad = 0;
#pragma unroll
          for (int i = 0; i < 12; i++) bad |= pq[i][0] ^ tag;
          if (!__any_sync(0xffffffffu, bad & 1)) { DBGIT(2, it); break; }
#pragma unroll
          for (int s = 0; s < 3; s++) {
            const int src = (akq + 3 - s) & 3;
#pragma unroll
            for (int i = 0; i < 4; i++) { if (RP & 2) ld_pkt(pin + src * 1024 + i * ISTR, pq[4 * s + i]); else re_pkt(pin + src * 1024 + i * ISTR, pq[4 * s + i], tag); }
          }
        }
      }
      mbar_arrive_if(BAR(B_DONE), lead);
      STAMPT(27);
      SCLKC(118);
#pragma unroll
      for (int s = 0; s < 3; s++)
#pragma unroll
        for (int i = 0; i < 4; i++) {
          const uint32_t* a = pq[4 * s + i];
#pragma unroll
          for (int e = 0; e < 4; e++) {
            const uint32_t w = (e || NOMASK) ? a[e] : (a[0] & ~1u);
            keep[8 * i + 2 * e] += __uint_as_float(w << 16);
            keep[8 * i + 2 * e + 1] += __uint_as_float(w & 0xffff0000u);
          }
        }
      stage64(sbase + 16384 + wg * 8192, keep, wq, lane);
      fence_async_smem();
      __syncwarp();
      mbar_arrive_if(BAR(B_HLP + 4) + wg * 8, lane == 0);
      if (threadIdx.x == 128) STAMP(10);
    }
  }
#undef BAR
}

typedef CUresult (*EncodeFn)(CUtensorMap*, CUtensorMapDataType, cuuint32_t, void*, const cuuint64_t*, const cuuint64_t*, const cuuint32_t*,
                             const cuuint32_t*, CUtensorMapInterleave, CUtensorMapSwizzle, CUtensorMapL2promotion, CUtensorMapFloatOOBfill);

static void enc(EncodeFn fn, CUtensorMap* m, const void* ptr, int rank, const cuuint64_t* dims, const cuuint64_t* strides, const cuuint32_t* box,
                CUtensorMapSwizzle sw) {
  cuuint32_t es[3] = {1, 1, 1};
  fn(m, CU_TENSOR_MAP_DATA_TYPE_BFLOAT16, rank, const_cast<void*>(ptr), dims, strides, box, es, CU_TENSOR_MAP_INTERLEAVE_NONE, sw,
     CU_TENSOR_MAP_L2_PROMOTION_L2_256B, CU_TENSOR_MAP_FLOAT_OOB_FILL_NONE);
}
static void enc2(EncodeFn fn, CUtensorMap* m, const void* ptr, uint64_t rows, uint64_t cols, uint64_t ld, uint32_t brows, uint32_t bcols) {
  cuuint64_t dims[2] = {cols, rows}, st[1] = {ld * 2};
  cuuint32_t box[2] = {bcols, brows};
  enc(fn, m, ptr, 2, dims, st, box, CU_TENSOR_MAP_SWIZZLE_128B);
}

}

extern "C" void kernel_launch(void* const* d_in, const int* in_sizes, int n_in, void* d_out, int out_size) {
  using namespace fk;
  static Params P;
  static bool init = false;
  static void* last_in[8];
  static void* last_out;
  bool same = init && last_out == d_out;
  for (int i = 0; i < 8 && same; i++) same = last_in[i] == d_in[i];
  if (!same) {
    void* p = nullptr;
    cudaDriverEntryPointQueryResult qr;
    cudaGetDriverEntryPoint("cuTensorMapEncodeTiled", &p, cudaEnableDefault, &qr);
    EncodeFn fn = (EncodeFn)p;
    void* ab;
    cudaGetSymbolAddress(&ab, g_ab);
    enc2(fn, &P.xa, d_in[0], 2048, 512, 512, 128, 64);
    enc2(fn, &P.wsre, d_in[1], 2048, 2048, 2048, 128, 64);
    enc2(fn, &P.wsim, d_in[2], 2048, 2048, 2048, 128, 64);
    enc2(fn, &P.wdre, d_in[3], 512, 512, 512, 128, 64);
    enc2(fn, &P.wdim, d_in[4], 512, 512, 512, 128, 64);
    enc2(fn, &P.xb, d_in[5], 2048, 512, 512, 128, 64);
    {
      cuuint64_t dims[3] = {512, 512, 3}, st[2] = {3072, 1024};
      cuuint32_t box[3] = {64, 32, 3};
      enc(fn, &P.wqkv, d_in[6], 3, dims, st, box, CU_TENSOR_MAP_SWIZZLE_128B);
    }
    {
      cuuint64_t dims[3] = {64, 512, 8}, st[2] = {1024, 128};
      cuuint32_t box[3] = {64, 64, 2};
      enc(fn, &P.wo, d_in[7], 3, dims, st, box, CU_TENSOR_MAP_SWIZZLE_128B);
    }
    {
      cuuint64_t dims[3] = {64, 4096, 8}, st[2] = {1024, 128};
      cuuint32_t box[3] = {64, 32, 4};
      enc(fn, &P.abld, ab, 3, dims, st, box, CU_TENSOR_MAP_SWIZZLE_128B);
    }
    enc2(fn, &P.abst, ab, 4096, 512, 512, ABR, 64);
    enc2(fn, &P.out, d_out, 2048, 1024, 1024, 64, 64);
    P.p_wsre = d_in[1]; P.p_wsim = d_in[2]; P.p_xa = d_in[0]; P.p_wdre = d_in[3]; P.p_wdim = d_in[4];
    cudaFuncSetAttribute(fused_kernel, cudaFuncAttributeMaxDynamicSharedMemorySize, SMEM_BYTES);
    for (int i = 0; i < 8; i++) last_in[i] = d_in[i];
    last_out = d_out;
    init = true;
  }
  fused_kernel<<<NCTA, 384, SMEM_BYTES, cudaStreamPerThread>>>(P);
}
```
